```python
import torch

def _softmax(x, axis=-1):
    return torch.softmax(x, dim=axis)
def _gelu(x):
    return torch.nn.functional.gelu(x, approximate="tanh")
def _silu(x):
    return torch.nn.functional.silu(x)
def _sigmoid(x):
    return torch.sigmoid(x)
def _layernorm(x, axis=-1, eps=1e-5):
    m = x.mean(dim=axis, keepdim=True)
    v = x.var(dim=axis, keepdim=True, unbiased=False)
    return (x - m) / torch.sqrt(v + eps)
def _scatter_add(tgt, idx, src, axis=0):
    return tgt.clone().index_add_(axis, idx, src)
def _segment_sum(src, seg, n):
    out = torch.zeros((n,) + src.shape[1:], dtype=src.dtype)
    return out.index_add_(0, seg, src)
def _pad(x, pw):
    flat = tuple(v for pair in reversed(pw) for v in pair)
    return torch.nn.functional.pad(x, flat)

kernel_name = 'concat_heads__grouped_kv_mqa__ssm_conv_s4d__prompt'

def setup_inputs():

    _w = (lambda a: (lambda t: t.to(torch.bfloat16) if t.is_floating_point() else t)(torch.as_tensor(a)))
    def _A_setup():
        B, S, D, H = 1, 2048, 448, 16
        Dh = D // H
        return {
            "x": _w((lambda *s: torch.randn(*s, dtype=torch.bfloat16) * 0.05)(B, S, D)),
            "wq": _w((lambda *s: torch.randn(*s, dtype=torch.bfloat16) * 1.6)(D, H * Dh)),
            "wk": _w((lambda *s: torch.randn(*s, dtype=torch.bfloat16) * 1.6)(D, Dh)),
            "wv": _w((lambda *s: torch.randn(*s, dtype=torch.bfloat16) * 0.05)(D, Dh)),
            "wo": _w((lambda *s: torch.randn(*s, dtype=torch.bfloat16) * 0.05)(H * Dh, D)),
        }
    _A_in = _A_setup()

    def _B_setup():
        Bsz, L, D, N = 1, 2048, 448, 256
        return {
            "u": _w((lambda *s: torch.randn(*s, dtype=torch.bfloat16) * 0.05)(Bsz, L, D)),
            "log_A_real": _w((lambda *s: torch.randn(*s, dtype=torch.bfloat16) * 3.2)(D, N) * 0.5),
            "A_imag": _w((lambda *s: torch.randn(*s, dtype=torch.bfloat16) * 0.05)(D, N) * 3.14),
            "C_real": _w((lambda *s: torch.randn(*s, dtype=torch.bfloat16) * 0.8)(D, N) / N ** 0.5),
            "C_imag": _w((lambda *s: torch.randn(*s, dtype=torch.bfloat16) * 0.8)(D, N) / N ** 0.5),
            "log_dt": _w((lambda *s: torch.randn(*s, dtype=torch.bfloat16) * 0.05)(D) * 0.5 - 4.0),
            "D_skip": _w((lambda *s: torch.randn(*s, dtype=torch.bfloat16) * 0.1)(D)),
        }
    _B_in = _B_setup()

    return {
        "A_x": _A_in["x"],
        "A_wq": _A_in["wq"],
        "A_wk": _A_in["wk"],
        "A_wv": _A_in["wv"],
        "A_wo": _A_in["wo"],
        "B_u": _B_in["u"],
        "B_log_A_real": _B_in["log_A_real"],
        "B_A_imag": _B_in["A_imag"],
        "B_C_real": _B_in["C_real"],
        "B_C_imag": _B_in["C_imag"],
        "B_log_dt": _B_in["log_dt"],
        "B_D_skip": _B_in["D_skip"],
    }

def reference(A_x, A_wq, A_wk, A_wv, A_wo, B_u, B_log_A_real, B_A_imag, B_C_real, B_C_imag, B_log_dt, B_D_skip):
    def _A_ref(x, wq, wk, wv, wo):
        B, S, D = x.shape
        H = 16
        Dh = D // H
        q = (lambda x, *d: x.permute(*d))((x @ wq).reshape(B, S, H, Dh), 0, 2, 1, 3)
        k = x @ wk
        v = x @ wv
        scores = torch.einsum("bhqd,bkd->bhqk", q, k) * (Dh ** -0.5)
        p = _softmax(scores, axis=-1)
        o = torch.einsum("bhqk,bkd->bhqd", p, v)
        return (lambda x, *d: x.permute(*d))(o, 0, 2, 1, 3).reshape(B, S, H * Dh) @ wo

    def _B_ref(u, log_A_real, A_imag, C_real, C_imag, log_dt, D_skip):
        L = u.shape[1]
        dt = torch.exp(log_dt)
        A = -torch.exp(log_A_real) + 1j * A_imag
        C = (C_real + 1j * C_imag) * dt[:, None]
        pos = (lambda x, dt: x.to(dt))(torch.arange(L), log_dt.dtype)
        P = torch.exp((A * dt[:, None])[:, :, None] * pos[None, None, :])
        K = 2.0 * torch.einsum("dn,dnl->dl", C, P).real
        L2 = 2 * L
        u_t = (lambda x, *d: x.permute(*d))(u, 0, 2, 1)
        Kf = (lambda x, *a, **k: torch.fft.rfft(x.float(), *a, **k))(K, L2)
        Uf = (lambda x, *a, **k: torch.fft.rfft(x.float(), *a, **k))(u_t, L2)
        y = (lambda x, *a, **k: torch.fft.irfft(x, *a, **k).to(torch.bfloat16))(Uf * Kf[None, :, :], L2)[:, :, :L]
        y = (lambda x, *d: x.permute(*d))(y, 0, 2, 1)
        return y + u * D_skip[None, None, :]

    a = _A_ref(A_x, A_wq, A_wk, A_wv, A_wo)
    b = _B_ref(B_u, B_log_A_real, B_A_imag, B_C_real, B_C_imag, B_log_dt, B_D_skip)
    return torch.concatenate([a, b], axis=-1)
```

```cpp
#include <cuda_runtime.h>
#include <cuda_bf16.h>
#include <cuda_fp16.h>
#include <cuda.h>
#include <stdint.h>

namespace {

constexpr int SEQ = 2048, DM = 448, DH = 28;
constexpr int NMAIN = 128, NCTA = 132, NTHR = 512;
constexpr uint32_t POLY_MASK = 0x5555u;

constexpr int OFF_BAR = 0;
constexpr int OFF_RING = 1024;
constexpr int SLOT = 16384, NSLOT = 5;
constexpr int OFF_W = OFF_RING + NSLOT * SLOT;
constexpr int WCS = 7168;
constexpr int SREG = 29696;
constexpr int OFF_S0 = OFF_W + 57344;
constexpr int OFF_O = OFF_S0 + 2 * SREG;
constexpr int SMEM_BYTES = OFF_S0 + 3 * SREG + 3072;
constexpr int B_FULL = 0, B_EMPTY = 5, B_READY = 10, B_WO = 11, B_OFULL = 12, B_UX = 13;
constexpr int OFF_MISC = 256;
constexpr int IT_U = 7, IT_KV = 9, IT_WO = 25;
constexpr int XCS = 4096;
constexpr int R_KP = 0, R_RV0 = 4096, R_RV1 = 8320 + 64, R_U = 24576, U_HS = 2176, R_MISC = 28928;

struct Params {
    CUtensorMap tm_x, tm_u, tm_wo64, tm_wo32;
    const __nv_bfloat16 *u, *wq, *wk, *wv, *lar, *aim, *cre, *cim, *ldt, *dsk;
    __nv_bfloat16* out;
};

__device__ __align__(1024) uint8_t g_kv[16 * SLOT];
__device__ __align__(128) __nv_bfloat16 g_q[SEQ * DM];
__device__ unsigned long long g_flags[NMAIN];
__device__ unsigned int g_done;
#define TS(i)

__device__ __forceinline__ uint32_t smem_u32(const void* p) { return (uint32_t)__cvta_generic_to_shared(p); }
__device__ __forceinline__ uint64_t make_desc(uint32_t addr, uint32_t lbo, uint32_t sbo, uint32_t swz) {
    return (uint64_t)((addr & 0x3FFFF) >> 4) | ((uint64_t)(lbo >> 4) << 16) | ((uint64_t)(sbo >> 4) << 32) | ((uint64_t)swz << 62);
}
__device__ __forceinline__ void wg_fence() { asm volatile("wgmma.fence.sync.aligned;" ::: "memory"); }
__device__ __forceinline__ void wg_commit() { asm volatile("wgmma.commit_group.sync.aligned;" ::: "memory"); }
template <int N> __device__ __forceinline__ void wg_wait() { asm volatile("wgmma.wait_group.sync.aligned %0;" ::"n"(N) : "memory"); }
template <int N> __device__ __forceinline__ void fence_regs(float (&r)[N]) {
#pragma unroll
    for (int i = 0; i < N; i++) asm volatile("" : "+f"(r[i])::"memory");
}
__device__ __forceinline__ void fence_async_smem() { asm volatile("fence.proxy.async.shared::cta;" ::: "memory"); }
__device__ __forceinline__ void fence_async_all() { asm volatile("fence.proxy.async;" ::: "memory"); }
__device__ __forceinline__ void bar_sync(int id, int n) { asm volatile("bar.sync %0, %1;" ::"r"(id), "r"(n) : "memory"); }
__device__ __forceinline__ void mbar_init(uint32_t a, uint32_t cnt) { asm volatile("mbarrier.init.shared::cta.b64 [%0], %1;" ::"r"(a), "r"(cnt) : "memory"); }
__device__ __forceinline__ void mbar_expect_tx(uint32_t a, uint32_t bytes) {
    asm volatile("mbarrier.arrive.expect_tx.shared::cta.b64 _, [%0], %1;" ::"r"(a), "r"(bytes) : "memory");
}
__device__ __forceinline__ void mbar_arrive(uint32_t a) { asm volatile("mbarrier.arrive.shared::cta.b64 _, [%0];" ::"r"(a) : "memory"); }
__device__ __forceinline__ uint32_t mapa(uint32_t a, uint32_t rank) {
    uint32_t r; asm("mapa.shared::cluster.u32 %0, %1, %2;" : "=r"(r) : "r"(a), "r"(rank)); return r;
}
__device__ __forceinline__ void mbar_arrive_cluster(uint32_t ca, uint32_t cnt) {
    asm volatile("mbarrier.arrive.release.cluster.shared::cluster.b64 _, [%0], %1;" ::"r"(ca), "r"(cnt) : "memory");
}
__device__ __forceinline__ bool mbar_try(uint32_t a, uint32_t parity) {
    uint32_t ok;
    asm volatile("{\n.reg .pred p;\nmbarrier.try_wait.parity.acquire.cluster.shared::cta.b64 p, [%1], %2;\nselp.u32 %0, 1, 0, p;\n}\n"
                 : "=r"(ok) : "r"(a), "r"(parity) : "memory");
    return ok;
}
__device__ __forceinline__ bool mbar_test(uint32_t a, uint32_t parity) {
    uint32_t ok;
    asm volatile("{\n.reg .pred p;\nmbarrier.test_wait.parity.acquire.cluster.shared::cta.b64 p, [%1], %2;\nselp.u32 %0, 1, 0, p;\n}\n"
                 : "=r"(ok) : "r"(a), "r"(parity) : "memory");
    return ok;
}
__device__ __forceinline__ void mbar_wait(uint32_t a, uint32_t parity) {
    if (mbar_try(a, parity)) return;
    for (int i = 0; i < (1 << 22); i++)
        if (mbar_try(a, parity)) return;
    __trap();
}
__device__ __forceinline__ void tma2d(uint32_t dst, const CUtensorMap* tm, int c0, int c1, uint32_t bar) {
    asm volatile("cp.async.bulk.tensor.2d.shared::cluster.global.mbarrier::complete_tx::bytes [%0], [%1, {%3, %4}], [%2];"
                 ::"r"(dst), "l"(tm), "r"(bar), "r"(c0), "r"(c1) : "memory");
}
__device__ __forceinline__ void tma2d_mc(uint32_t dst, const CUtensorMap* tm, int c0, int c1, uint32_t bar) {
    asm volatile("cp.async.bulk.tensor.2d.shared::cluster.global.mbarrier::complete_tx::bytes.multicast::cluster [%0], [%1, {%3, %4}], [%2], %5;"
                 ::"r"(dst), "l"(tm), "r"(bar), "r"(c0), "r"(c1), "h"((uint16_t)3) : "memory");
}
__device__ __forceinline__ void bulk_mc(uint32_t dst, const void* src, uint32_t bytes, uint32_t bar) {
    asm volatile("cp.async.bulk.shared::cluster.global.mbarrier::complete_tx::bytes.multicast::cluster [%0], [%1], %2, [%3], %4;"
                 ::"r"(dst), "l"(src), "r"(bytes), "r"(bar), "h"((uint16_t)3) : "memory");
}
__device__ __forceinline__ void bulk_s2s(uint32_t dst_cluster, uint32_t src, uint32_t bytes, uint32_t bar_cluster) {
    asm volatile("cp.async.bulk.shared::cluster.shared::cta.mbarrier::complete_tx::bytes [%0], [%1], %2, [%3];"
                 ::"r"(dst_cluster), "r"(src), "r"(bytes), "r"(bar_cluster) : "memory");
}
__device__ __forceinline__ void cp_async16(uint32_t dst, const void* src) { asm volatile("cp.async.cg.shared.global [%0], [%1], 16;" ::"r"(dst), "l"(src) : "memory"); }
__device__ __forceinline__ void cp_async8(uint32_t dst, const void* src) { asm volatile("cp.async.ca.shared.global [%0], [%1], 8;" ::"r"(dst), "l"(src) : "memory"); }
__device__ __forceinline__ void cp_commit() { asm volatile("cp.async.commit_group;" ::: "memory"); }
template <int N> __device__ __forceinline__ void cp_wait() { asm volatile("cp.async.wait_group %0;" ::"n"(N) : "memory"); }
__device__ __forceinline__ void cluster_arrive() { asm volatile("barrier.cluster.arrive.aligned;" ::: "memory"); }
__device__ __forceinline__ void cluster_wait() { asm volatile("barrier.cluster.wait.aligned;" ::: "memory"); }
__device__ __forceinline__ void sts32(uint32_t a, uint32_t v) { asm volatile("st.shared.u32 [%0], %1;" ::"r"(a), "r"(v) : "memory"); }
__device__ __forceinline__ void sts16(uint32_t a, uint16_t v) { asm volatile("st.shared.u16 [%0], %1;" ::"r"(a), "h"(v) : "memory"); }
__device__ __forceinline__ void sts128(uint32_t a, uint32_t x, uint32_t y, uint32_t z, uint32_t w) {
    asm volatile("st.shared.v4.u32 [%0], {%1,%2,%3,%4};" ::"r"(a), "r"(x), "r"(y), "r"(z), "r"(w) : "memory");
}
__device__ __forceinline__ uint32_t lds32(uint32_t a) { uint32_t v; asm volatile("ld.shared.u32 %0, [%1];" : "=r"(v) : "r"(a) : "memory"); return v; }
__device__ __forceinline__ uint32_t lds16(uint32_t a) { uint16_t v; asm volatile("ld.shared.u16 %0, [%1];" : "=h"(v) : "r"(a) : "memory"); return v; }
__device__ __forceinline__ float4 lds128f(uint32_t a) {
    float4 v; asm volatile("ld.shared.v4.f32 {%0,%1,%2,%3}, [%4];" : "=f"(v.x), "=f"(v.y), "=f"(v.z), "=f"(v.w) : "r"(a) : "memory"); return v;
}
__device__ __forceinline__ float ex2f(float x) { float y; asm("ex2.approx.ftz.f32 %0, %1;" : "=f"(y) : "f"(x)); return y; }
__device__ __forceinline__ uint32_t pack_bf16(float lo, float hi) { uint32_t r; asm("cvt.rn.bf16x2.f32 %0, %1, %2;" : "=r"(r) : "f"(hi), "f"(lo)); return r; }
__device__ __forceinline__ uint32_t pack_f16(float lo, float hi) { uint32_t r; asm("cvt.rn.f16x2.f32 %0, %1, %2;" : "=r"(r) : "f"(hi), "f"(lo)); return r; }
__device__ __forceinline__ uint32_t hfma2(uint32_t a, uint32_t b, uint32_t c) { uint32_t r; asm("fma.rn.f16x2 %0, %1, %2, %3;" : "=r"(r) : "r"(a), "r"(b), "r"(c)); return r; }
__device__ __forceinline__ float bf_lo(uint32_t v) { return __uint_as_float(v << 16); }
__device__ __forceinline__ float bf_hi(uint32_t v) { return __uint_as_float(v & 0xFFFF0000u); }
__device__ __forceinline__ float bf16r(float x) { return __bfloat162float(__float2bfloat16_rn(x)); }
__device__ __forceinline__ float ldbf(const __nv_bfloat16* p) { return __bfloat162float(__ldg(p)); }

__device__ __forceinline__ void wg_qk(float (&d)[32], const uint32_t (&a)[4], uint64_t descB, int sc) {
    asm volatile("{\n.reg .pred p;\nsetp.ne.b32 p, %37, 0;\n"
        "wgmma.mma_async.sync.aligned.m64n64k16.f32.bf16.bf16 {%0,%1,%2,%3,%4,%5,%6,%7,%8,%9,%10,%11,%12,%13,%14,%15,%16,%17,%18,%19,%20,%21,%22,%23,%24,%25,%26,%27,%28,%29,%30,%31}, {%32,%33,%34,%35}, %36, p, 1, 1, 0;\n}\n"
        : "+f"(d[0]), "+f"(d[1]), "+f"(d[2]), "+f"(d[3]), "+f"(d[4]), "+f"(d[5]), "+f"(d[6]), "+f"(d[7]), "+f"(d[8]), "+f"(d[9]), "+f"(d[10]), "+f"(d[11]), "+f"(d[12]), "+f"(d[13]), "+f"(d[14]), "+f"(d[15]), "+f"(d[16]), "+f"(d[17]), "+f"(d[18]), "+f"(d[19]), "+f"(d[20]), "+f"(d[21]), "+f"(d[22]), "+f"(d[23]), "+f"(d[24]), "+f"(d[25]), "+f"(d[26]), "+f"(d[27]), "+f"(d[28]), "+f"(d[29]), "+f"(d[30]), "+f"(d[31])
        : "r"(a[0]), "r"(a[1]), "r"(a[2]), "r"(a[3]), "l"(descB), "r"(sc));
}
__device__ __forceinline__ void wg_pv(float (&d)[16], const uint32_t (&a)[4], uint64_t descB, int sc) {
    asm volatile("{\n.reg .pred p;\nsetp.ne.b32 p, %21, 0;\n"
        "wgmma.mma_async.sync.aligned.m64n32k16.f32.bf16.bf16 {%0,%1,%2,%3,%4,%5,%6,%7,%8,%9,%10,%11,%12,%13,%14,%15}, {%16,%17,%18,%19}, %20, p, 1, 1, 1;\n}\n"
        : "+f"(d[0]), "+f"(d[1]), "+f"(d[2]), "+f"(d[3]), "+f"(d[4]), "+f"(d[5]), "+f"(d[6]), "+f"(d[7]), "+f"(d[8]), "+f"(d[9]), "+f"(d[10]), "+f"(d[11]), "+f"(d[12]), "+f"(d[13]), "+f"(d[14]), "+f"(d[15])
        : "r"(a[0]), "r"(a[1]), "r"(a[2]), "r"(a[3]), "l"(descB), "r"(sc));
}
__device__ __forceinline__ void wg_proj(float (&d)[32], uint64_t descA, uint64_t descB, int sc) {
    asm volatile("{\n.reg .pred p;\nsetp.ne.b32 p, %34, 0;\n"
        "wgmma.mma_async.sync.aligned.m64n64k16.f32.bf16.bf16 {%0,%1,%2,%3,%4,%5,%6,%7,%8,%9,%10,%11,%12,%13,%14,%15,%16,%17,%18,%19,%20,%21,%22,%23,%24,%25,%26,%27,%28,%29,%30,%31}, %32, %33, p, 1, 1, 0, 1;\n}\n"
        : "+f"(d[0]), "+f"(d[1]), "+f"(d[2]), "+f"(d[3]), "+f"(d[4]), "+f"(d[5]), "+f"(d[6]), "+f"(d[7]), "+f"(d[8]), "+f"(d[9]), "+f"(d[10]), "+f"(d[11]), "+f"(d[12]), "+f"(d[13]), "+f"(d[14]), "+f"(d[15]), "+f"(d[16]), "+f"(d[17]), "+f"(d[18]), "+f"(d[19]), "+f"(d[20]), "+f"(d[21]), "+f"(d[22]), "+f"(d[23]), "+f"(d[24]), "+f"(d[25]), "+f"(d[26]), "+f"(d[27]), "+f"(d[28]), "+f"(d[29]), "+f"(d[30]), "+f"(d[31])
        : "l"(descA), "l"(descB), "r"(sc));
}
__device__ __forceinline__ void wg_oproj(float (&d)[16], uint64_t descA, uint64_t descB, int sc) {
    asm volatile("{\n.reg .pred p;\nsetp.ne.b32 p, %18, 0;\n"
        "wgmma.mma_async.sync.aligned.m64n32k16.f32.bf16.bf16 {%0,%1,%2,%3,%4,%5,%6,%7,%8,%9,%10,%11,%12,%13,%14,%15}, %16, %17, p, 1, 1, 1, 0;\n}\n"
        : "+f"(d[0]), "+f"(d[1]), "+f"(d[2]), "+f"(d[3]), "+f"(d[4]), "+f"(d[5]), "+f"(d[6]), "+f"(d[7]), "+f"(d[8]), "+f"(d[9]), "+f"(d[10]), "+f"(d[11]), "+f"(d[12]), "+f"(d[13]), "+f"(d[14]), "+f"(d[15])
        : "l"(descA), "l"(descB), "r"(sc));
}
__device__ __forceinline__ void wg_kgen_p(float (&d)[8], uint64_t descA, uint64_t descB, int sc) {
    asm volatile("{\n.reg .pred p;\nsetp.ne.b32 p, %10, 0;\n"
        "wgmma.mma_async.sync.aligned.m64n16k16.f32.f16.f16 {%0,%1,%2,%3,%4,%5,%6,%7}, %8, %9, p, 1, 1, 1, 1;\n}\n"
        : "+f"(d[0]), "+f"(d[1]), "+f"(d[2]), "+f"(d[3]), "+f"(d[4]), "+f"(d[5]), "+f"(d[6]), "+f"(d[7])
        : "l"(descA), "l"(descB), "r"(sc));
}
__device__ __forceinline__ void wg_kgen_n(float (&d)[8], uint64_t descA, uint64_t descB, int sc) {
    asm volatile("{\n.reg .pred p;\nsetp.ne.b32 p, %10, 0;\n"
        "wgmma.mma_async.sync.aligned.m64n16k16.f32.f16.f16 {%0,%1,%2,%3,%4,%5,%6,%7}, %8, %9, p, 1, -1, 1, 1;\n}\n"
        : "+f"(d[0]), "+f"(d[1]), "+f"(d[2]), "+f"(d[3]), "+f"(d[4]), "+f"(d[5]), "+f"(d[6]), "+f"(d[7])
        : "l"(descA), "l"(descB), "r"(sc));
}
__device__ __forceinline__ void wg_conv0(float (&d)[64], const uint32_t (&a)[4], uint64_t descB, int sc) {
    asm volatile("{\n.reg .pred p;\nsetp.ne.b32 p, %69, 0;\n"
        "wgmma.mma_async.sync.aligned.m64n128k16.f32.bf16.bf16 {%0,%1,%2,%3,%4,%5,%6,%7,%8,%9,%10,%11,%12,%13,%14,%15,%16,%17,%18,%19,%20,%21,%22,%23,%24,%25,%26,%27,%28,%29,%30,%31,%32,%33,%34,%35,%36,%37,%38,%39,%40,%41,%42,%43,%44,%45,%46,%47,%48,%49,%50,%51,%52,%53,%54,%55,%56,%57,%58,%59,%60,%61,%62,%63}, {%64,%65,%66,%67}, %68, p, 1, 1, 0;\n}\n"
        : "+f"(d[0]), "+f"(d[1]), "+f"(d[2]), "+f"(d[3]), "+f"(d[4]), "+f"(d[5]), "+f"(d[6]), "+f"(d[7]), "+f"(d[8]), "+f"(d[9]), "+f"(d[10]), "+f"(d[11]), "+f"(d[12]), "+f"(d[13]), "+f"(d[14]), "+f"(d[15]), "+f"(d[16]), "+f"(d[17]), "+f"(d[18]), "+f"(d[19]), "+f"(d[20]), "+f"(d[21]), "+f"(d[22]), "+f"(d[23]), "+f"(d[24]), "+f"(d[25]), "+f"(d[26]), "+f"(d[27]), "+f"(d[28]), "+f"(d[29]), "+f"(d[30]), "+f"(d[31]), "+f"(d[32]), "+f"(d[33]), "+f"(d[34]), "+f"(d[35]), "+f"(d[36]), "+f"(d[37]), "+f"(d[38]), "+f"(d[39]), "+f"(d[40]), "+f"(d[41]), "+f"(d[42]), "+f"(d[43]), "+f"(d[44]), "+f"(d[45]), "+f"(d[46]), "+f"(d[47]), "+f"(d[48]), "+f"(d[49]), "+f"(d[50]), "+f"(d[51]), "+f"(d[52]), "+f"(d[53]), "+f"(d[54]), "+f"(d[55]), "+f"(d[56]), "+f"(d[57]), "+f"(d[58]), "+f"(d[59]), "+f"(d[60]), "+f"(d[61]), "+f"(d[62]), "+f"(d[63])
        : "r"(a[0]), "r"(a[1]), "r"(a[2]), "r"(a[3]), "l"(descB), "r"(sc));
}
__device__ __forceinline__ void wg_conv1(float (&d)[64], const uint32_t (&a)[4], uint64_t descB, int sc) {
    asm volatile("{\n.reg .pred p;\nsetp.ne.b32 p, %53, 0;\n"
        "wgmma.mma_async.sync.aligned.m64n96k16.f32.bf16.bf16 {%0,%1,%2,%3,%4,%5,%6,%7,%8,%9,%10,%11,%12,%13,%14,%15,%16,%17,%18,%19,%20,%21,%22,%23,%24,%25,%26,%27,%28,%29,%30,%31,%32,%33,%34,%35,%36,%37,%38,%39,%40,%41,%42,%43,%44,%45,%46,%47}, {%48,%49,%50,%51}, %52, p, 1, 1, 0;\n}\n"
        : "+f"(d[16]), "+f"(d[17]), "+f"(d[18]), "+f"(d[19]), "+f"(d[20]), "+f"(d[21]), "+f"(d[22]), "+f"(d[23]), "+f"(d[24]), "+f"(d[25]), "+f"(d[26]), "+f"(d[27]), "+f"(d[28]), "+f"(d[29]), "+f"(d[30]), "+f"(d[31]), "+f"(d[32]), "+f"(d[33]), "+f"(d[34]), "+f"(d[35]), "+f"(d[36]), "+f"(d[37]), "+f"(d[38]), "+f"(d[39]), "+f"(d[40]), "+f"(d[41]), "+f"(d[42]), "+f"(d[43]), "+f"(d[44]), "+f"(d[45]), "+f"(d[46]), "+f"(d[47]), "+f"(d[48]), "+f"(d[49]), "+f"(d[50]), "+f"(d[51]), "+f"(d[52]), "+f"(d[53]), "+f"(d[54]), "+f"(d[55]), "+f"(d[56]), "+f"(d[57]), "+f"(d[58]), "+f"(d[59]), "+f"(d[60]), "+f"(d[61]), "+f"(d[62]), "+f"(d[63])
        : "r"(a[0]), "r"(a[1]), "r"(a[2]), "r"(a[3]), "l"(descB), "r"(sc));
}
__device__ __forceinline__ void wg_conv2(float (&d)[64], const uint32_t (&a)[4], uint64_t descB, int sc) {
    asm volatile("{\n.reg .pred p;\nsetp.ne.b32 p, %37, 0;\n"
        "wgmma.mma_async.sync.aligned.m64n64k16.f32.bf16.bf16 {%0,%1,%2,%3,%4,%5,%6,%7,%8,%9,%10,%11,%12,%13,%14,%15,%16,%17,%18,%19,%20,%21,%22,%23,%24,%25,%26,%27,%28,%29,%30,%31}, {%32,%33,%34,%35}, %36, p, 1, 1, 0;\n}\n"
        : "+f"(d[32]), "+f"(d[33]), "+f"(d[34]), "+f"(d[35]), "+f"(d[36]), "+f"(d[37]), "+f"(d[38]), "+f"(d[39]), "+f"(d[40]), "+f"(d[41]), "+f"(d[42]), "+f"(d[43]), "+f"(d[44]), "+f"(d[45]), "+f"(d[46]), "+f"(d[47]), "+f"(d[48]), "+f"(d[49]), "+f"(d[50]), "+f"(d[51]), "+f"(d[52]), "+f"(d[53]), "+f"(d[54]), "+f"(d[55]), "+f"(d[56]), "+f"(d[57]), "+f"(d[58]), "+f"(d[59]), "+f"(d[60]), "+f"(d[61]), "+f"(d[62]), "+f"(d[63])
        : "r"(a[0]), "r"(a[1]), "r"(a[2]), "r"(a[3]), "l"(descB), "r"(sc));
}
__device__ __forceinline__ void wg_conv3(float (&d)[64], const uint32_t (&a)[4], uint64_t descB, int sc) {
    asm volatile("{\n.reg .pred p;\nsetp.ne.b32 p, %21, 0;\n"
        "wgmma.mma_async.sync.aligned.m64n32k16.f32.bf16.bf16 {%0,%1,%2,%3,%4,%5,%6,%7,%8,%9,%10,%11,%12,%13,%14,%15}, {%16,%17,%18,%19}, %20, p, 1, 1, 0;\n}\n"
        : "+f"(d[48]), "+f"(d[49]), "+f"(d[50]), "+f"(d[51]), "+f"(d[52]), "+f"(d[53]), "+f"(d[54]), "+f"(d[55]), "+f"(d[56]), "+f"(d[57]), "+f"(d[58]), "+f"(d[59]), "+f"(d[60]), "+f"(d[61]), "+f"(d[62]), "+f"(d[63])
        : "r"(a[0]), "r"(a[1]), "r"(a[2]), "r"(a[3]), "l"(descB), "r"(sc));
}

struct cpx { float r, i; };
__device__ __forceinline__ cpx cmul(cpx a, cpx b) { return {fmaf(a.r, b.r, -a.i * b.i), fmaf(a.r, b.i, a.i * b.r)}; }
__device__ __forceinline__ cpx csqr(cpx a) { return {fmaf(a.r, a.r, -a.i * a.i), (a.r + a.r) * a.i}; }
__device__ __forceinline__ cpx cexp_at(float zl, float zt, float p) {
    float mag = ex2f(zl * p);
    float t = zt * p;
    t = (t - rintf(t)) * 6.283185307179586f;
    return {mag * __cosf(t), mag * __sinf(t)};
}
struct h2c { __half2 r, i; };
__device__ __forceinline__ h2c hpack(cpx a, cpx b) { return {__floats2half2_rn(a.r, b.r), __floats2half2_rn(a.i, b.i)}; }
__device__ __forceinline__ h2c hmul(h2c a, __half2 e) {
    __half2 er = __low2half2(e), ei = __high2half2(e);
    h2c o;
    o.r = __hfma2(a.r, er, __hneg2(__hmul2(a.i, ei)));
    o.i = __hfma2(a.r, ei, __hmul2(a.i, er));
    return o;
}
__device__ __forceinline__ __half2 epack(cpx e) { return __floats2half2_rn(e.r, e.i); }
__device__ __forceinline__ uint32_t h2u(__half2 h) { return *reinterpret_cast<uint32_t*>(&h); }

struct KgenVals { h2c x[20], y[8]; float k2048; };
__device__ __forceinline__ void kgen_mode(float zr, float zi, cpx c, KgenVals& v) {
    const float zl = zr * 1.4426950408889634f, zt = zi * 0.15915494309189535f;
    cpx e1 = cexp_at(zl, zt, 1.f), e8 = cexp_at(zl, zt, 8.f), e64 = cexp_at(zl, zt, 64.f), e512 = cexp_at(zl, zt, 512.f);
    cpx e2 = csqr(e1), e3 = cmul(e2, e1), e4 = csqr(e2), e5 = cmul(e4, e1), e6 = csqr(e3), e7 = cmul(e4, e3);
    cpx e16 = csqr(e8), e24 = cmul(e16, e8), e32 = csqr(e16), e96 = cmul(e64, e32);
    cpx e128 = csqr(e64), e256 = csqr(e128), e384 = cmul(e256, e128);
    cpx e1024 = csqr(e512), e1536 = cmul(e1024, e512), e2048 = csqr(e1024);
    v.k2048 = fmaf(c.r, e2048.r, -c.i * e2048.i);
    v.y[0] = hpack({1.f, 0.f}, e8); v.y[1] = hpack(e16, e24);
    __half2 m = epack(e32);  v.y[2] = hmul(v.y[0], m); v.y[3] = hmul(v.y[1], m);
    m = epack(e64);          v.y[4] = hmul(v.y[0], m); v.y[5] = hmul(v.y[1], m);
    m = epack(e96);          v.y[6] = hmul(v.y[0], m); v.y[7] = hmul(v.y[1], m);
    v.x[0] = hpack(c, cmul(c, e128)); v.x[1] = hpack(cmul(c, e256), cmul(c, e384));
    m = epack(e512);         v.x[2] = hmul(v.x[0], m); v.x[3] = hmul(v.x[1], m);
    m = epack(e1024);        v.x[4] = hmul(v.x[0], m); v.x[5] = hmul(v.x[1], m);
    m = epack(e1536);        v.x[6] = hmul(v.x[0], m); v.x[7] = hmul(v.x[1], m);
    m = epack(e4);
#pragma unroll
    for (int i = 0; i < 4; i++) v.x[8 + i] = hmul(v.x[i], m);
    m = epack(e2);           v.x[12] = hmul(v.x[0], m); v.x[13] = hmul(v.x[1], m);
    m = epack(e6);           v.x[14] = hmul(v.x[0], m); v.x[15] = hmul(v.x[1], m);
    v.x[16] = hmul(v.x[0], epack(e1)); v.x[17] = hmul(v.x[0], epack(e3));
    v.x[18] = hmul(v.x[0], epack(e5)); v.x[19] = hmul(v.x[0], epack(e7));
}
__device__ __forceinline__ void kgen_store(uint32_t R, int tid, const KgenVals& v) {
    uint32_t ar = R + tid * 16, ai = ar + 2048;
#pragma unroll
    for (int c = 0; c < 5; c++) {
        sts128(ar + c * XCS, h2u(v.x[4 * c].r), h2u(v.x[4 * c + 1].r), h2u(v.x[4 * c + 2].r), h2u(v.x[4 * c + 3].r));
        sts128(ai + c * XCS, h2u(v.x[4 * c].i), h2u(v.x[4 * c + 1].i), h2u(v.x[4 * c + 2].i), h2u(v.x[4 * c + 3].i));
    }
#pragma unroll
    for (int c = 0; c < 2; c++) {
        sts128(ar + (5 + c) * XCS, h2u(v.y[4 * c].r), h2u(v.y[4 * c + 1].r), h2u(v.y[4 * c + 2].r), h2u(v.y[4 * c + 3].r));
        sts128(ai + (5 + c) * XCS, h2u(v.y[4 * c].i), h2u(v.y[4 * c + 1].i), h2u(v.y[4 * c + 2].i), h2u(v.y[4 * c + 3].i));
    }
}
__device__ __forceinline__ void kgen_mma(uint32_t R, float (&acc)[8], int first) {
    uint64_t da = make_desc(R, 128, XCS, 0), db = make_desc(R + 5 * XCS, 128, XCS, 0);
    wg_fence();
#pragma unroll
    for (int ks = 0; ks < 8; ks++) wg_kgen_p(acc, da + ks * 16, db + ks * 16, (ks > 0) | !first);
#pragma unroll
    for (int ks = 8; ks < 16; ks++) wg_kgen_n(acc, da + ks * 16, db + ks * 16, 1);
    wg_commit();
}
__device__ __forceinline__ int rowpos(int m) {
    if (m < 16) return 128 * m;
    if (m < 24) return 128 * (m - 16) + 4;
    if (m < 32) return 128 * (m & 3) + 2 + ((m & 4));
    return 128 * (m & 1) + 1 + (m & 6);
}
__device__ __forceinline__ uint32_t kp_off(uint32_t bits16) { return 2u * (uint32_t)max((int)bits16 - 0x3F7F, 0); }

struct SsmRegs { float lar[2], aim[2], cre[2], cim[2], ldt, dsk; };
__device__ __forceinline__ void ssm_load(const Params& P, int d, int tid, SsmRegs& s) {
#pragma unroll
    for (int i = 0; i < 2; i++) {
        int o = d * 256 + i * 128 + tid;
        s.lar[i] = ldbf(P.lar + o); s.aim[i] = ldbf(P.aim + o); s.cre[i] = ldbf(P.cre + o); s.cim[i] = ldbf(P.cim + o);
    }
    s.ldt = ldbf(P.ldt + d); s.dsk = ldbf(P.dsk + d);
}

__device__ __forceinline__ void ssm_kgen(const SsmRegs& s, uint32_t R, int tid, int bar, const __nv_bfloat16* ucol) {
    const int lane = tid & 31, w = tid >> 5, g = lane >> 2, t = lane & 3;
    const float dt = bf16r(expf(s.ldt));
    float cm = fmaxf(fmaxf(fabsf(s.cre[0]), fabsf(s.cim[0])), fmaxf(fabsf(s.cre[1]), fabsf(s.cim[1])));
#pragma unroll
    for (int o = 16; o; o >>= 1) cm = fmaxf(cm, __shfl_xor_sync(~0u, cm, o));
    if (lane == 0) sts32(R + R_MISC + w * 4, __float_as_uint(cm));
    bar_sync(bar, 128);
    float4 cm4 = lds128f(R + R_MISC);
    cm = fmaxf(fmaxf(cm4.x, cm4.y), fmaxf(cm4.z, cm4.w));
    int ce = min(max((int)(__float_as_uint(cm) >> 23), 20), 240);
    const float sc = __uint_as_float((uint32_t)(263 - ce) << 23);
    const float mult = 2.f * dt * __uint_as_float((uint32_t)(ce - 9) << 23);
    float acc[8];
    float k2048;
    {
        KgenVals v;
        kgen_mode(-bf16r(expf(s.lar[0])) * dt, s.aim[0] * dt, {s.cre[0] * sc, s.cim[0] * sc}, v);
        k2048 = v.k2048;
        kgen_store(R, tid, v);
        fence_async_smem();
        bar_sync(bar, 128);
        kgen_mma(R, acc, 1);
    }
    {
        KgenVals v;
        kgen_mode(-bf16r(expf(s.lar[1])) * dt, s.aim[1] * dt, {s.cre[1] * sc, s.cim[1] * sc}, v);
        k2048 += v.k2048;
        wg_wait<0>();
        bar_sync(bar, 128);
        kgen_store(R, tid, v);
        fence_async_smem();
        bar_sync(bar, 128);
        kgen_mma(R, acc, 0);
    }
#pragma unroll
    for (int o = 16; o; o >>= 1) k2048 += __shfl_xor_sync(~0u, k2048, o);
    if (lane == 0) sts32(R + R_MISC + 16 + w * 4, __float_as_uint(k2048));
    uint16_t ud[16];
    if (ucol) {
#pragma unroll
        for (int i = 0; i < 16; i++) ud[i] = __ldg((const uint16_t*)ucol + (size_t)(16 * tid + i) * DM);
    }
    wg_wait<0>();
    fence_regs(acc);
    bar_sync(bar, 128);
#pragma unroll
    for (int h = 0; h < 2; h++) {
        int m = 16 * w + 8 * h + g;
        if (m < 40) {
            int p0 = rowpos(m) + 16 * t;
#pragma unroll
            for (int jb = 0; jb < 2; jb++) {
                uint32_t pb = pack_bf16((float)(p0 + 64 * jb), (float)(p0 + 64 * jb + 8));
                uint32_t kv = pack_bf16(acc[4 * jb + 2 * h] * mult, acc[4 * jb + 2 * h + 1] * mult);
                sts16(R + R_KP + kp_off(pb & 0xFFFF), (uint16_t)(kv & 0xFFFF));
                sts16(R + R_KP + kp_off(pb >> 16), (uint16_t)(kv >> 16));
            }
        }
    }
    if (tid == 127) {
        float4 k4 = lds128f(R + R_MISC + 16);
        sts16(R + R_KP + kp_off(0x4500), (uint16_t)(pack_bf16((k4.x + k4.y + k4.z + k4.w) * mult, 0.f) & 0xFFFF));
    }
    bar_sync(bar, 128);
    {
        uint32_t v[18];
        const float f0 = (float)(2049 - 16 * tid);
#pragma unroll
        for (int q = 0; q < 18; q += 2) {
            uint32_t pb = pack_bf16(f0 - (float)q, f0 - (float)(q + 1));
            v[q] = lds16(R + R_KP + kp_off(pb & 0xFFFF));
            if (q < 16) v[q + 1] = lds16(R + R_KP + kp_off(pb >> 16));
        }
        uint32_t a0 = R + R_RV0 + tid * 32, a1 = R + R_RV1 + tid * 32;
#pragma unroll
        for (int h = 0; h < 2; h++) {
            const int q = 8 * h;
            sts128(a1 + 16 * h, v[q] | (v[q + 1] << 16), v[q + 2] | (v[q + 3] << 16), v[q + 4] | (v[q + 5] << 16), v[q + 6] | (v[q + 7] << 16));
            sts128(a0 + 16 * h, v[q + 1] | (v[q + 2] << 16), v[q + 3] | (v[q + 4] << 16), v[q + 5] | (v[q + 6] << 16), v[q + 7] | (v[q + 8] << 16));
        }
        if (tid < 2) {
            uint32_t k0 = lds16(R + R_KP), k1 = lds16(R + R_KP + 2);
            uint32_t a = (tid ? R + R_RV1 : R + R_RV0) + 4096;
            sts128(a, tid ? (k1 | (k0 << 16)) : k0, 0, 0, 0);
            sts128(a + 16, 0, 0, 0, 0);
            sts128(a + 32, 0, 0, 0, 0);
        }
        if (tid >= 32 && tid < 48) sts128(R + R_U + (tid & 8 ? U_HS : 0) + (tid & 7) * 16, 0, 0, 0, 0);
    }
    if (ucol) {
#pragma unroll
        for (int h = 0; h < 2; h++)
            sts128(R + R_U + h * U_HS + (tid + 8) * 16, ud[8 * h] | ((uint32_t)ud[8 * h + 1] << 16), ud[8 * h + 2] | ((uint32_t)ud[8 * h + 3] << 16),
                   ud[8 * h + 4] | ((uint32_t)ud[8 * h + 5] << 16), ud[8 * h + 6] | ((uint32_t)ud[8 * h + 7] << 16));
    }
}

__device__ __forceinline__ void ssm_gather_u(uint32_t R, uint32_t stage, int row0, int ch, int tid) {
    const int lane = tid & 31, w = tid >> 5, g = lane >> 2, t = lane & 3;
    const int mi = lane >> 3, rho = lane & 7;
    const uint32_t src = stage + (uint32_t)(8 * (rho >> 1) + 2 * mi + (rho & 1)) * 16 + w * 4096;
#pragma unroll
    for (int it = 0; it < 8; it++) {
        uint32_t r0, r1, r2, r3;
        asm volatile("ldmatrix.sync.aligned.m8n8.x4.trans.shared.b16 {%0,%1,%2,%3}, [%4];"
                     : "=r"(r0), "=r"(r1), "=r"(r2), "=r"(r3) : "r"(src + it * 512) : "memory");
        int kap = (row0 + w * 256 + it * 32) / 8 + t;
        if (g == ch) sts128(R + R_U + (kap & 1) * U_HS + ((kap >> 1) + 8) * 16, r0, r1, r2, r3);
    }
}

template <int A> __device__ __forceinline__ void conv_mma(float (&acc)[64], const uint32_t (&a)[4], uint64_t db, int sc) {
    if (A == 0) wg_conv0(acc, a, db, sc);
    if (A == 1) wg_conv1(acc, a, db, sc);
    if (A == 2) wg_conv2(acc, a, db, sc);
    if (A == 3) wg_conv3(acc, a, db, sc);
}
__device__ __forceinline__ void conv_ldA(uint32_t (&a)[4][4], uint32_t fb) {
#pragma unroll
    for (int e = 0; e < 4; e++) {
        a[e][0] = lds32(fb - 32 * e); a[e][1] = lds32(fb - 32 * e - 16); a[e][2] = lds32(fb - 32 * e + 16); a[e][3] = lds32(fb - 32 * e);
    }
}
template <int A> __device__ __forceinline__ void conv_stage(float (&acc)[64], uint32_t (&a0)[4][4], uint32_t (&a1)[4][4], uint32_t fb, uint64_t db) {
    wg_fence();
#pragma unroll
    for (int e = 0; e < 4; e++) conv_mma<A>(acc, a0[e], db - e, (A > 0) | (e > 0));
    wg_commit();
    conv_ldA(a1, fb - 32 * (32 * A + 4));
    wg_fence();
#pragma unroll
    for (int e = 0; e < 4; e++) conv_mma<A>(acc, a1[e], db - 4 - e, 1);
    wg_commit();
    wg_wait<1>();
    if (A < 3) conv_ldA(a0, fb - 32 * (32 * (A + 1)));
    wg_wait<0>();
}
__device__ __forceinline__ void ssm_conv(const Params& P, uint32_t R, int d, float dsk, int tid, int bar) {
    const int lane = tid & 31, w = tid >> 5, g = lane >> 2, t = lane & 3;
    fence_async_smem();
    bar_sync(bar, 128);
    float acc[64];
    uint32_t a0[4][4], a1[4][4];
    const uint32_t fb = ((g & 1) ? R + R_RV1 + 2 * (2049 - g + 2 * t) : R + R_RV0 + 2 * (2048 - g + 2 * t)) - 256 * w;
    const uint64_t db = make_desc(R + R_U + 128, U_HS, 128, 0);
    conv_ldA(a0, fb);
    conv_stage<0>(acc, a0, a1, fb, db);
    conv_stage<1>(acc, a0, a1, fb, db);
    conv_stage<2>(acc, a0, a1, fb, db);
    conv_stage<3>(acc, a0, a1, fb, db);
    fence_regs(acc);
    bar_sync(bar, 128);
#pragma unroll
    for (int b = 0; b < 16; b++)
        if (b & 3)
            sts128(R + ((w * 12 + (b >> 2) * 3 + (b & 3) - 1) * 32 + lane) * 16, __float_as_uint(acc[4 * b]), __float_as_uint(acc[4 * b + 1]),
                   __float_as_uint(acc[4 * b + 2]), __float_as_uint(acc[4 * b + 3]));
    bar_sync(bar, 128);
    __nv_bfloat16* o = P.out + DM + d;
#pragma unroll
    for (int i = 0; i < 4; i++) {
        float y0 = acc[16 * i], y1 = acc[16 * i + 1], y2 = acc[16 * i + 2], y3 = acc[16 * i + 3];
        const int J = 4 * i + w;
#pragma unroll
        for (int k = 1; k < 4; k++) {
            int ws = (w + k) & 3, b = J - ws;
            if (b >= 0) {
                float4 p = lds128f(R + ((ws * 12 + (b >> 2) * 3 + (b & 3) - 1) * 32 + lane) * 16);
                y0 += p.x; y1 += p.y; y2 += p.z; y3 += p.w;
            }
        }
        const int i1 = 8 * J + 2 * t;
        const float y[4] = {y0, y1, y2, y3};
#pragma unroll
        for (int e = 0; e < 4; e++) {
            int c = i1 + (e & 1), h = e >> 1;
            float u = __uint_as_float(lds16(R + R_U + h * U_HS + (c + 8) * 16 + 2 * g) << 16);
            o[(size_t)(16 * c + 8 * h + g) * (2 * DM)] = __float2bfloat16_rn(bf16r(y[e]) + bf16r(u * dsk));
        }
    }
}

struct ExpC { uint32_t one, c3; };
__device__ __forceinline__ uint32_t ex2_pair(float lo, float hi, const ExpC& c) {
    uint32_t w; asm("cvt.pack.sat.u16.s32 %0, %1, %2;" : "=r"(w) : "r"(__float_as_int(hi)), "r"(__float_as_int(lo)));
    uint32_t m; asm("lop3.b32 %0, %1, 0x03FF03FF, %2, 0xEA;" : "=r"(m) : "r"(w), "r"(c.one));
    uint32_t e = w & 0xFC00FC00u;
    uint32_t q = hfma2(c.c3, m, 0x9EEC9EECu);
    q = hfma2(q, m, 0x379E379Eu);
    q = hfma2(q, m, 0x483A483Au);
    return (e >> 3) + q;
}
template <uint32_t MASK>
__device__ __forceinline__ void softmax_block(const float (&s)[32], uint32_t (&p)[4][4], const ExpC& c) {
#pragma unroll
    for (int i = 0; i < 32; i += 2) {
        const bool poly = (MASK >> (i / 4)) & 1;
        p[i / 8][(i % 8) / 2] = poly ? ex2_pair(s[i], s[i + 1], c) : pack_bf16(ex2f(s[i]), ex2f(s[i + 1]));
    }
}
__device__ __forceinline__ void pv_block(float (&o)[16], uint32_t (&p)[4][4], uint64_t dv) {
#pragma unroll
    for (int kk = 0; kk < 4; kk++) wg_pv(o, p[kk], dv + kk * 16, 1);
}

__device__ __noinline__ void attn_fallback(uint32_t omat, int pos0, int h, int grp0, int lane) {
    for (int r = 0; r < 16; r++) {
        float q[DH];
#pragma unroll
        for (int c = 0; c < DH; c++) q[c] = __bfloat162float(g_q[(size_t)(pos0 + r) * DM + h * DH + c]) * 0x1p60f;
        float m = -INFINITY, l = 0.f, o[DH];
#pragma unroll
        for (int c = 0; c < DH; c++) o[c] = 0.f;
        for (int j = lane; j < SEQ; j += 32) {
            const uint8_t* base = g_kv + (j >> 7) * SLOT + (j & 127) * 16;
            const float ks = ((POLY_MASK >> ((j >> 3) & 15)) & 1) ? 0x1p79f : 0x1p-60f;
            float s = 0.f;
#pragma unroll
            for (int c = 0; c < DH; c += 2) {
                uint32_t kk = *(const uint32_t*)(base + (c >> 3) * 2048 + (c & 7) * 2);
                s = fmaf(q[c], bf_lo(kk) * ks, s); s = fmaf(q[c + 1], bf_hi(kk) * ks, s);
            }
            float mn = fmaxf(m, s);
            float corr = (m == -INFINITY) ? 0.f : exp2f(m - mn), p = exp2f(s - mn);
            m = mn; l = l * corr + p;
#pragma unroll
            for (int c = 0; c < DH; c += 2) {
                uint32_t vv = *(const uint32_t*)(base + 8192 + (c >> 3) * 2048 + (c & 7) * 2);
                o[c] = fmaf(p, bf_lo(vv), o[c] * corr); o[c + 1] = fmaf(p, bf_hi(vv), o[c + 1] * corr);
            }
        }
        float mt = m;
#pragma unroll
        for (int s = 16; s; s >>= 1) mt = fmaxf(mt, __shfl_xor_sync(~0u, mt, s));
        float f = exp2f(m - mt);
        l *= f;
#pragma unroll
        for (int s = 16; s; s >>= 1) l += __shfl_xor_sync(~0u, l, s);
        float inv = 1.f / l;
#pragma unroll
        for (int c = 0; c < DH; c++) {
            float x = o[c] * f;
#pragma unroll
            for (int s = 16; s; s >>= 1) x += __shfl_xor_sync(~0u, x, s);
            if (lane == 0) {
                int k = h * DH + c;
                sts16(omat + (grp0 + (r >> 3)) * 7168 + (k >> 3) * 128 + (r & 7) * 16 + (k & 7) * 2, (uint16_t)(pack_bf16(x * inv, 0.f) & 0xFFFF));
            }
        }
    }
}

__device__ __forceinline__ uint32_t wo_box(int w, int kc, int& late) {
    late = -1;
    if (w < 3) {
        int idx = kc * 3 + w;
        if (idx < 7) return OFF_W + idx * 8192;
        if (idx < 10) return OFF_S0 + (idx - 7) * 8192;
        if (idx < 13) return OFF_S0 + SREG + (idx - 10) * 8192;
        late = 1 + ((idx - 13) >> 1);
        return OFF_RING + ((IT_WO + late) % NSLOT) * SLOT + ((idx - 13) & 1) * 8192;
    }
    if (kc == 0) return OFF_S0 + 24576;
    if (kc == 1) return OFF_S0 + SREG + 24576;
    if (kc == 2) return OFF_O + 28672;
    late = 0;
    return OFF_RING + (IT_WO % NSLOT) * SLOT + (kc - 3) * 4096;
}
__device__ __forceinline__ void wo_issue(const Params& P, uint32_t sb, int rank, int w, int kc, uint32_t bar) {
    int late;
    uint32_t a = sb + wo_box(w, kc, late);
    tma2d(a, w < 3 ? &P.tm_wo64 : &P.tm_wo32, 224 * rank + 64 * w, 64 * kc, bar);
}

__global__ void __cluster_dims__(2, 1, 1) __launch_bounds__(NTHR, 1) fused_kernel(const __grid_constant__ Params P) {
    extern __shared__ __align__(1024) uint8_t smem[];
    const uint32_t sb = smem_u32(smem);
    const int tid = threadIdx.x & 127, wg = threadIdx.x >> 7;
    const int lane = tid & 31, w = tid >> 5, g = lane >> 2, t = lane & 3;
    const int cta = blockIdx.x, rank = cta & 1;
    const uint32_t bars = sb + OFF_BAR;
    TS(0);

    if (cta >= NMAIN) {
        const int d0 = 3 * NMAIN + 16 * (cta - NMAIN);
        if (threadIdx.x == 0) {
            mbar_init(bars + 8 * B_UX, 1);
            fence_async_smem();
            mbar_expect_tx(bars + 8 * B_UX, 65536);
            for (int i = 0; i < 16; i++) tma2d(sb + OFF_RING + i * 4096, &P.tm_u, d0 + 8 * (i >> 3), 256 * (i & 7), bars + 8 * B_UX);
        }
        __syncthreads();
        const uint32_t R = sb + (wg < 3 ? OFF_S0 + wg * SREG : OFF_W);
        for (int r = 0; r < 4; r++) {
            const int c = 4 * r + wg;
            SsmRegs s;
            ssm_load(P, d0 + c, tid, s);
            ssm_kgen(s, R, tid, 1 + wg, nullptr);
            mbar_wait(bars + 8 * B_UX, 0);
            ssm_gather_u(R, sb + OFF_RING + (c >> 3) * 32768, 0, c & 7, tid);
            ssm_gather_u(R, sb + OFF_RING + (c >> 3) * 32768 + 16384, 1024, c & 7, tid);
            ssm_conv(P, R, d0 + c, s.dsk, tid, 1 + wg);
            bar_sync(1 + wg, 128);
        }
        TS(9);
        return;
    }

    const int cl = cta >> 1;
    const int pb = cl >> 2, pj = 2 * (cl & 3) + rank;
    if (threadIdx.x == 0) {
        for (int i = 0; i < NSLOT; i++) { mbar_init(bars + 8 * (B_FULL + i), 1); mbar_init(bars + 8 * (B_EMPTY + i), 32); }
        mbar_init(bars + 8 * B_READY, 1);
        mbar_init(bars + 8 * B_WO, 4);
        mbar_init(bars + 8 * B_OFULL, 5);
        asm volatile("fence.mbarrier_init.release.cluster;" ::: "memory");
        fence_async_smem();
    }
    __syncthreads();
    cluster_arrive();
    const uint32_t peer_bars = mapa(bars, rank ^ 1), self_bars = mapa(bars, rank);
    auto release = [&](int item, int cnt) {
        mbar_arrive_cluster(self_bars + 8 * (B_EMPTY + item % NSLOT), cnt);
        mbar_arrive_cluster(peer_bars + 8 * (B_EMPTY + item % NSLOT), cnt);
    };
    const int rot = cl & 15;
    auto issue_item = [&](int n) {
        const uint32_t slot = sb + OFF_RING + (n % NSLOT) * SLOT, fb = bars + 8 * (B_FULL + n % NSLOT);
        mbar_expect_tx(fb, SLOT);
        if (n < IT_U) {
            tma2d_mc(slot + rank * 8192, &P.tm_x, 64 * n, 128 * pb + 64 * rank, fb);
        } else if (n < IT_KV) {
            for (int i = 0; i < 4; i++) tma2d(slot + i * 4096, &P.tm_u, (3 * cta + 1) & ~7, 1024 * (n - IT_U) + 256 * i, fb);
        } else if (n < IT_WO) {
            bulk_mc(slot + rank * 8192, g_kv + (((n - IT_KV) + rot) & 15) * SLOT + rank * 8192, 8192, fb);
        } else if (n == IT_WO) {
            for (int kc = 3; kc < 7; kc++) wo_issue(P, sb, rank, 3, kc, fb);
        } else {
            for (int i = 0; i < 2; i++) { int idx = 13 + 2 * (n - IT_WO - 1) + i; wo_issue(P, sb, rank, idx % 3, idx / 3, fb); }
        }
    };
    auto wait_empty = [&](int n) { if (n >= NSLOT) mbar_wait(bars + 8 * (B_EMPTY + n % NSLOT), (n / NSLOT - 1) & 1); };
    auto test_empty = [&](int n) { return mbar_test(bars + 8 * (B_EMPTY + n % NSLOT), (n / NSLOT - 1) & 1); };
    auto wait_full = [&](int n) { mbar_wait(bars + 8 * (B_FULL + n % NSLOT), (n / NSLOT) & 1); };
    int next_item = 0;

    if (wg == 0) {
        {
            const int kr = lane & 7, cq = lane >> 3;
            const int qcol0 = pj < 2 ? 32 * pj - 32 : 64 * (pj - 1);
            const __nv_bfloat16* wkv = pj == 0 ? P.wk : P.wv;
            for (int kc = 0; kc < 7; kc++) {
#pragma unroll
                for (int i = 0; i < 4; i++) {
                    const int k = 64 * kc + 16 * w + 8 * (i >> 1) + kr, c = 4 * (i & 1) + cq;
                    const uint32_t dst = sb + OFF_W + c * WCS + k * 16;
                    if (pj < 2 && c < 4) {
                        cp_async8(dst, wkv + k * DH + 8 * c);
                        if (c < 3) cp_async8(dst + 8, wkv + k * DH + 8 * c + 4);
                        else asm volatile("st.shared.v2.u32 [%0], {%1,%1};" ::"r"(dst + 8), "r"(0) : "memory");
                    } else {
                        cp_async16(dst, P.wq + k * DM + qcol0 + 8 * c);
                    }
                }
                cp_commit();
            }
        }
        cluster_wait();
        if (tid == 0) for (; next_item < NSLOT; next_item++) issue_item(next_item);
        float acc0[32], acc1[32];
#pragma unroll
        for (int kc = 0; kc < 7; kc++) {
            switch (kc) {
                case 0: cp_wait<6>(); break; case 1: cp_wait<5>(); break; case 2: cp_wait<4>(); break; case 3: cp_wait<3>(); break;
                case 4: cp_wait<2>(); break; case 5: cp_wait<1>(); break; default: cp_wait<0>(); break;
            }
            fence_async_smem();
            bar_sync(1, 128);
            wait_full(kc);
            const uint64_t da = make_desc(sb + OFF_RING + (kc % NSLOT) * SLOT, 16, 1024, 1);
            const uint64_t db = make_desc(sb + OFF_W + kc * 1024, 128, WCS, 0);
            wg_fence();
#pragma unroll
            for (int ks = 0; ks < 4; ks++) {
                wg_proj(acc0, da + ks * 2, db + ks * 16, (kc > 0) | (ks > 0));
                wg_proj(acc1, da + 512 + ks * 2, db + ks * 16, (kc > 0) | (ks > 0));
            }
            wg_commit();
            wg_wait<0>();
            bar_sync(1, 128);
            if (tid == 0) {
                release(kc, 16);
                if (next_item < IT_KV) { wait_empty(next_item); issue_item(next_item); next_item++; }
            }
        }
        fence_regs(acc0); fence_regs(acc1);
        TS(1);
        float red = 0.f;
        {
            const float cq = 0.27264379719888306f * 0x1p-60f;
            const int qcol0 = pj < 2 ? 32 * pj - 32 : 64 * (pj - 1);
#pragma unroll
            for (int hh = 0; hh < 4; hh++) {
                const int row = 64 * (hh >> 1) + 16 * w + 8 * (hh & 1) + g;
                float nrm = 0.f;
                const bool poly = (POLY_MASK >> (row >> 3)) & 1;
                const float ks = pj == 0 ? (poly ? 0x1p-79f : 0x1p60f) : 1.f;
#pragma unroll
                for (int jb = 0; jb < 8; jb++) {
                    const float a = (hh >> 1) ? acc1[4 * jb + 2 * (hh & 1)] : acc0[4 * jb + 2 * (hh & 1)];
                    const float b = (hh >> 1) ? acc1[4 * jb + 2 * (hh & 1) + 1] : acc0[4 * jb + 2 * (hh & 1) + 1];
                    if (pj < 2 && jb < 4) {
                        uint32_t v = pack_bf16(a, b);
                        float x = bf_lo(v), y = bf_hi(v);
                        if (pj == 0) nrm = fmaf(x, x, fmaf(y, y, nrm)); else nrm = fmaxf(nrm, fmaxf(fabsf(x), fabsf(y)));
                        if (jb == 3 && t == 2) { x = 1.f; y = (pj == 0 && !poly) ? 18.f : 0.f; }
                        *(uint32_t*)(g_kv + pb * SLOT + pj * 8192 + jb * 2048 + row * 16 + 4 * t) = pack_bf16(x * ks, y * ks);
                    } else {
                        *(uint32_t*)(g_q + (size_t)(128 * pb + row) * DM + qcol0 + 8 * jb + 2 * t) = pack_bf16(a * cq, b * cq);
                    }
                }
                if (pj == 0) { nrm += __shfl_xor_sync(~0u, nrm, 1); nrm += __shfl_xor_sync(~0u, nrm, 2); }
                red = (nrm > red || nrm != nrm) ? nrm : red;
            }
#pragma unroll
            for (int o = 16; o; o >>= 1) { float x = __shfl_xor_sync(~0u, red, o); red = (x > red || x != x) ? x : red; }
            if (lane == 0) sts32(sb + OFF_MISC + 4 * w, __float_as_uint(red));
        }
        fence_async_all();
        __threadfence();
        bar_sync(1, 128);
        if (tid == 0) {
            float4 r4 = lds128f(sb + OFF_MISC);
            uint32_t m = max(max(__float_as_uint(r4.x), __float_as_uint(r4.y)), max(__float_as_uint(r4.z), __float_as_uint(r4.w)));
            asm volatile("st.release.gpu.global.u64 [%0], %1;" ::"l"(g_flags + cta), "l"((1ull << 32) | m) : "memory");
            mbar_expect_tx(bars + 8 * B_WO, 7 * 8192);
            for (int idx = 0; idx < 7; idx++) wo_issue(P, sb, rank, idx % 3, idx / 3, bars + 8 * B_WO);
            mbar_expect_tx(bars + 8 * B_OFULL, 14336);
        }
        TS(2);
        {
            unsigned long long f;
            int it = 0;
            do {
                asm volatile("ld.acquire.gpu.global.u64 %0, [%1];" : "=l"(f) : "l"(g_flags + tid) : "memory");
                if (++it > (1 << 22)) __trap();
            } while (!(f >> 32));
            uint32_t km = (tid & 7) == 0 ? (uint32_t)f : 0u, vm = (tid & 7) == 1 ? (uint32_t)f : 0u;
            km = __reduce_max_sync(~0u, km); vm = __reduce_max_sync(~0u, vm);
            if (lane == 0) { sts32(sb + OFF_MISC + 16 + 4 * w, km); sts32(sb + OFF_MISC + 32 + 4 * w, vm); }
            bar_sync(1, 128);
            if (tid == 0) {
                fence_async_all();
                mbar_arrive(bars + 8 * B_READY);
                while (next_item < IT_KV + 3) { wait_empty(next_item); issue_item(next_item); next_item++; }
                if (atomicAdd(&g_done, 1u) == NMAIN - 1) {
                    for (int i = 0; i < NMAIN; i++) g_flags[i] = 0ull;
                    g_done = 0u;
                }
            }
        }
        TS(3);
    } else {
        const int d = 3 * cta + wg - 1;
        const uint32_t R = sb + OFF_S0 + (wg - 1) * SREG;
        SsmRegs s;
        ssm_load(P, d, tid, s);
        cluster_wait();
        const bool direct = (d >> 3) != ((3 * cta + 1) >> 3);
        ssm_kgen(s, R, tid, 1 + wg, direct ? P.u + d : nullptr);
        TS(1);
#pragma unroll
        for (int i = 0; i < 2; i++) {
            wait_full(IT_U + i);
            if (!direct) ssm_gather_u(R, sb + OFF_RING + ((IT_U + i) % NSLOT) * SLOT, 1024 * i, d & 7, tid);
        }
        bar_sync(1 + wg, 128);
        if (tid == 0) { release(IT_U, wg == 1 ? 8 : 4); release(IT_U + 1, wg == 1 ? 8 : 4); }
        TS(2);
        ssm_conv(P, R, d, s.dsk, tid, 1 + wg);
        fence_async_smem();
        bar_sync(1 + wg, 128);
        if (tid == 0) {
            if (wg < 3) {
                mbar_expect_tx(bars + 8 * B_WO, 3 * 8192 + 4096);
                for (int idx = 4 + 3 * wg; idx < 7 + 3 * wg; idx++) wo_issue(P, sb, rank, idx % 3, idx / 3, bars + 8 * B_WO);
            } else {
                mbar_expect_tx(bars + 8 * B_WO, 4096);
            }
            wo_issue(P, sb, rank, 3, wg - 1, bars + 8 * B_WO);
        }
        TS(3);
    }

    const int pos0 = 16 * cta, head = 4 * wg + w;
    mbar_wait(bars + 8 * B_READY, 0);
    uint32_t q0[4], q1[4];
    bool ok;
    {
        const uint32_t* qa = (const uint32_t*)(g_q + (size_t)(pos0 + g) * DM + head * DH) + t;
        const uint32_t* qb = qa + 8 * (DM / 2);
        q0[0] = __ldcg(qa); q0[1] = __ldcg(qb); q0[2] = __ldcg(qa + 4); q0[3] = __ldcg(qb + 4);
        q1[0] = __ldcg(qa + 8); q1[1] = __ldcg(qb + 8);
        q1[2] = t < 2 ? __ldcg(qa + 12) : 0u; q1[3] = t < 2 ? __ldcg(qb + 12) : 0u;
        float4 k4 = lds128f(sb + OFF_MISC + 16), v4 = lds128f(sb + OFF_MISC + 32);
        const float kmax2 = __uint_as_float(max(max(__float_as_uint(k4.x), __float_as_uint(k4.y)), max(__float_as_uint(k4.z), __float_as_uint(k4.w))));
        const float vmax = __uint_as_float(max(max(__float_as_uint(v4.x), __float_as_uint(v4.y)), max(__float_as_uint(v4.z), __float_as_uint(v4.w))));
        float n0 = 0.f, n1 = 0.f;
#pragma unroll
        for (int i = 0; i < 4; i += 2) {
            float a;
            a = bf_lo(q0[i]) * 0x1p60f; n0 = fmaf(a, a, n0); a = bf_hi(q0[i]) * 0x1p60f; n0 = fmaf(a, a, n0);
            a = bf_lo(q1[i]) * 0x1p60f; n0 = fmaf(a, a, n0); a = bf_hi(q1[i]) * 0x1p60f; n0 = fmaf(a, a, n0);
            a = bf_lo(q0[i + 1]) * 0x1p60f; n1 = fmaf(a, a, n1); a = bf_hi(q0[i + 1]) * 0x1p60f; n1 = fmaf(a, a, n1);
            a = bf_lo(q1[i + 1]) * 0x1p60f; n1 = fmaf(a, a, n1); a = bf_hi(q1[i + 1]) * 0x1p60f; n1 = fmaf(a, a, n1);
        }
        n0 += __shfl_xor_sync(~0u, n0, 1); n0 += __shfl_xor_sync(~0u, n0, 2);
        n1 += __shfl_xor_sync(~0u, n1, 1); n1 += __shfl_xor_sync(~0u, n1, 2);
        const float m0 = ceilf(sqrtf(n0 * kmax2) * 1.0001f + 0.25f), m1 = ceilf(sqrtf(n1 * kmax2) * 1.0001f + 0.25f);
        ok = (m0 <= 250.f) && (m1 <= 250.f) && (vmax <= 0x1p30f);
        if (t == 2) { q1[2] = pack_bf16((64.f - m0) * 0x1p-60f, 0x1p-60f); q1[3] = pack_bf16((64.f - m1) * 0x1p-60f, 0x1p-60f); }
    }
    float o[16];
#pragma unroll
    for (int i = 0; i < 16; i++) o[i] = 0.f;
    {
        ExpC ec; ec.one = 0x3C003C00u; ec.c3 = 0x2CFA2CFAu;
        asm volatile("" : "+r"(ec.one), "+r"(ec.c3));
        float sa[32], sbk[32];
        uint32_t pa[4][4], pbk[4][4];
        const uint64_t dk_base = make_desc(sb + OFF_RING, 2048, 128, 0), dv_base = make_desc(sb + OFF_RING + 8192, 128, 2048, 0);
        int slot = IT_KV % NSLOT, ph = (IT_KV / NSLOT) & 1;
        fence_regs(o);
        mbar_wait(bars + 8 * (B_FULL + slot), ph);
        TS(4);
        wg_fence();
        wg_qk(sa, q0, dk_base + slot * 1024, 0);
        wg_qk(sa, q1, dk_base + slot * 1024 + 256, 1);
        wg_commit();
        wg_wait<0>();
#pragma unroll 1
        for (int i = 0; i < 16; i++) {
            const uint64_t dk = dk_base + slot * 1024, dv = dv_base + slot * 1024;
            int nslot = slot + 1, nph = ph;
            if (nslot == NSLOT) { nslot = 0; nph ^= 1; }
            if (i == 15) nslot = slot;
            wg_fence();
            wg_qk(sbk, q0, dk + 64, 0);
            wg_qk(sbk, q1, dk + 64 + 256, 1);
            wg_commit();
            fence_regs(sa);
            softmax_block<(POLY_MASK & 255)>(sa, pa, ec);
            wg_fence();
            pv_block(o, pa, dv);
            wg_commit();
            wg_wait<1>();
            if (lane == 0) {
                if (i > 0) release(IT_KV + i - 1, 1);
                if (threadIdx.x == 0) {
                    while (next_item < IT_WO && (next_item <= IT_KV + i + 1 || test_empty(next_item))) {
                        wait_empty(next_item); issue_item(next_item); next_item++;
                    }
                }
            }
            if (i < 15) mbar_wait(bars + 8 * (B_FULL + nslot), nph);
            wg_fence();
            wg_qk(sa, q0, dk_base + nslot * 1024, 0);
            wg_qk(sa, q1, dk_base + nslot * 1024 + 256, 1);
            wg_commit();
            fence_regs(sbk);
            softmax_block<(POLY_MASK >> 8)>(sbk, pbk, ec);
            wg_fence();
            pv_block(o, pbk, dv + 64);
            wg_commit();
            wg_wait<1>();
            slot = nslot; ph = nph;
        }
        wg_wait<0>();
        fence_regs(o); fence_regs(sa);
    }
    TS(5);
    if (lane == 0) release(IT_KV + 15, 1);
    {
        const uint32_t omat = sb + OFF_O;
        const float l0 = __shfl_sync(~0u, o[12], (lane & ~3) + 2), l1 = __shfl_sync(~0u, o[14], (lane & ~3) + 2);
        ok = ok && (l0 >= 0x1p40f) && (l0 <= 0x1p120f) && (l1 >= 0x1p40f) && (l1 <= 0x1p120f);
        if (__all_sync(~0u, ok)) {
            const float i0 = 1.f / l0, i1 = 1.f / l1;
#pragma unroll
            for (int jb = 0; jb < 4; jb++) {
                if (jb < 3 || t < 2) {
                    const int k = head * DH + 8 * jb + 2 * t;
                    const uint32_t a = omat + (2 * rank) * 7168 + (k >> 3) * 128 + g * 16 + (k & 7) * 2;
                    sts32(a, pack_bf16(o[4 * jb] * i0, o[4 * jb + 1] * i0));
                    sts32(a + 7168, pack_bf16(o[4 * jb + 2] * i1, o[4 * jb + 3] * i1));
                }
            }
        } else {
            attn_fallback(omat, pos0, head, 2 * rank, lane);
        }
        fence_async_smem();
        bar_sync(1 + wg, 128);
        if (tid == 0) {
            const uint32_t src = omat + (2 * rank) * 7168 + wg * 1792;
            bulk_s2s(mapa(src, rank ^ 1), src, 1792, peer_bars + 8 * B_OFULL);
            bulk_s2s(mapa(src + 7168, rank ^ 1), src + 7168, 1792, peer_bars + 8 * B_OFULL);
            mbar_arrive(bars + 8 * B_OFULL);
            if (wg == 0) for (; next_item < IT_WO + 5; next_item++) { wait_empty(next_item); issue_item(next_item); }
        }
    }
    {
        float acc[16];
        mbar_wait(bars + 8 * B_WO, 0);
        mbar_wait(bars + 8 * B_OFULL, 0);
        TS(6);
        const uint64_t db = make_desc(sb + OFF_O, 128, 7168, 0);
        int seen = -1;
#pragma unroll 1
        for (int kc = 0; kc < 7; kc++) {
            int late;
            const uint32_t a = sb + wo_box(wg, kc, late);
            if (late > seen) { wait_full(IT_WO + late); seen = late; }
            const uint64_t da = wg < 3 ? make_desc(a, 0, 1024, 1) : make_desc(a, 0, 512, 2);
            const int astep = wg < 3 ? 128 : 64;
            wg_fence();
#pragma unroll
            for (int ks = 0; ks < 4; ks++) wg_oproj(acc, da + ks * astep, db + (kc * 4 + ks) * 16, (kc > 0) | (ks > 0));
            wg_commit();
        }
        wg_wait<0>();
        fence_regs(acc);
        TS(7);
        cluster_arrive();
        if (wg < 3 || w < 2) {
            __nv_bfloat16* ob = P.out + (size_t)(32 * cl) * (2 * DM) + 224 * rank + 64 * wg + 16 * w + g;
#pragma unroll
            for (int i = 0; i < 16; i++)
                ob[(size_t)(8 * (i >> 2) + 2 * t + (i & 1)) * (2 * DM) + 8 * ((i >> 1) & 1)] = __float2bfloat16_rn(acc[i]);
        }
        cluster_wait();
    }
    TS(8);
}

typedef CUresult (*EncodeFn)(CUtensorMap*, CUtensorMapDataType, cuuint32_t, void*, const cuuint64_t*, const cuuint64_t*,
                             const cuuint32_t*, const cuuint32_t*, CUtensorMapInterleave, CUtensorMapSwizzle,
                             CUtensorMapL2promotion, CUtensorMapFloatOOBfill);

void encode2d(EncodeFn fn, CUtensorMap* tm, const void* base, int rows, int boxc, int boxr, CUtensorMapSwizzle sw) {
    cuuint64_t dims[2] = {(cuuint64_t)DM, (cuuint64_t)rows};
    cuuint64_t strides[1] = {(cuuint64_t)DM * 2};
    cuuint32_t box[2] = {(cuuint32_t)boxc, (cuuint32_t)boxr};
    cuuint32_t es[2] = {1, 1};
    fn(tm, CU_TENSOR_MAP_DATA_TYPE_BFLOAT16, 2, const_cast<void*>(base), dims, strides, box, es, CU_TENSOR_MAP_INTERLEAVE_NONE, sw,
       CU_TENSOR_MAP_L2_PROMOTION_L2_128B, CU_TENSOR_MAP_FLOAT_OOB_FILL_NONE);
}

}

extern "C" void kernel_launch(void* const* d_in, const int* in_sizes, int n_in, void* d_out, int out_size) {
    static EncodeFn enc = nullptr;
    if (!enc) {
        void* fn = nullptr;
        cudaDriverEntryPointQueryResult st;
        cudaGetDriverEntryPoint("cuTensorMapEncodeTiled", &fn, cudaEnableDefault, &st);
        enc = (EncodeFn)fn;
        cudaFuncSetAttribute(fused_kernel, cudaFuncAttributeMaxDynamicSharedMemorySize, SMEM_BYTES);
    }
    Params P;
    encode2d(enc, &P.tm_x, d_in[0], SEQ, 64, 64, CU_TENSOR_MAP_SWIZZLE_128B);
    encode2d(enc, &P.tm_u, d_in[5], SEQ, 8, 256, CU_TENSOR_MAP_SWIZZLE_NONE);
    encode2d(enc, &P.tm_wo64, d_in[4], DM, 64, 64, CU_TENSOR_MAP_SWIZZLE_128B);
    encode2d(enc, &P.tm_wo32, d_in[4], DM, 32, 64, CU_TENSOR_MAP_SWIZZLE_64B);
    P.u = (const __nv_bfloat16*)d_in[5];
    P.wq = (const __nv_bfloat16*)d_in[1]; P.wk = (const __nv_bfloat16*)d_in[2]; P.wv = (const __nv_bfloat16*)d_in[3];
    P.lar = (const __nv_bfloat16*)d_in[6]; P.aim = (const __nv_bfloat16*)d_in[7];
    P.cre = (const __nv_bfloat16*)d_in[8]; P.cim = (const __nv_bfloat16*)d_in[9];
    P.ldt = (const __nv_bfloat16*)d_in[10]; P.dsk = (const __nv_bfloat16*)d_in[11];
    P.out = (__nv_bfloat16*)d_out;
    fused_kernel<<<NCTA, NTHR, SMEM_BYTES>>>(P);
}
```

```cpp
#include <cuda_runtime.h>
#include <cuda_bf16.h>
#include <cuda_fp16.h>
#include <cuda.h>
#include <stdint.h>

namespace {

constexpr int SEQ = 2048, DM = 448, DH = 28, QP = 456;
constexpr int NMAIN = 128, NCTA = 132, NTHR = 640;
constexpr uint32_t POLY_MASK = 0x6D55u;

constexpr int OFF_BAR = 0;
constexpr int OFF_RING = 1024;
constexpr int SLOT = 16384;
constexpr int OFF_W = OFF_RING + 4 * SLOT;
constexpr int SREG = 34816;
constexpr int OFF_S = OFF_W + 57344 - SREG;
constexpr int OFF_O = OFF_S + 3 * SREG;
constexpr int SMEM_BYTES = OFF_S + 4 * SREG + 4096;
constexpr int OFF_B0 = 1024;
constexpr int B_G = 0  , B_WKV = 3, B_KN = 7, B_GD = 8, B_U = 14, B_UALL = 16, B_YFREE = 17, B_READY = 18, B_WO = 19, B_KFULL = 20, B_KEMPTY = 24, B_RFREE = 28,
              B_QDONE = 29, B_Y = 30, B_OFULL = 32, B_YDONE = 36, B_GO = 37, B_STG = 38;
constexpr unsigned long long BARCNT0 = 0x119a037700ull, BARCNT1 = 0x719a007700ull, BARCNT2 = 0x710a000700ull, BARCNT3 = 0x710a000700ull;
constexpr int OFF_MISC = 448;
constexpr int R_KP = 0, R_RV0 = 4096, R_RV1 = 8320 + 64, R_MISC = 29696, R_U = 30464, U_HS = 2176;

struct Params {
    CUtensorMap tm_x, tm_u, tm_wo64, tm_wo32, tm_wq, tm_q, tm_y, tm_o64, tm_o32, tm_ut;
    const __nv_bfloat16 *wk, *wv, *lar, *aim, *cre, *cim, *ldt, *dsk;
    __nv_bfloat16* out;
};

__device__ __align__(1024) uint8_t g_kv[16 * SLOT];
__device__ __align__(128) __nv_bfloat16 g_q[SEQ * QP];
__device__ __align__(128) __nv_bfloat16 g_y[DM * 2176];
__device__ __align__(128) __nv_bfloat16 g_ut[DM * 2176];
__device__ __align__(128) unsigned int g_syn[40][32];
#define g_sync(i) g_syn[i][0]
#define TS(i)
#define TH(i)

__device__ __forceinline__ uint32_t smem_u32(const void* p) { return (uint32_t)__cvta_generic_to_shared(p); }
typedef unsigned long long Desc;
__device__ __forceinline__ Desc make_desc(uint32_t addr, uint32_t lbo, uint32_t sbo, uint32_t swz) {
    return (Desc)(((addr & 0x3FFFF) >> 4) | ((lbo >> 4) << 16)) | ((Desc)((sbo >> 4) | (swz << 30)) << 32);
}
__device__ __forceinline__ void wg_fence() { asm volatile("wgmma.fence.sync.aligned;" ::: "memory"); }
__device__ __forceinline__ void wg_commit() { asm volatile("wgmma.commit_group.sync.aligned;" ::: "memory"); }
template <int N> __device__ __forceinline__ void wg_wait() { asm volatile("wgmma.wait_group.sync.aligned %0;" ::"n"(N) : "memory"); }
template <int N> __device__ __forceinline__ void zero_regs(float (&r)[N]) {
#pragma unroll
    for (int i = 0; i < N; i++) { r[i] = 0.f; asm volatile("" : "+f"(r[i])::"memory"); }
}
template <int N> __device__ __forceinline__ void fence_regs(float (&r)[N]) {
#pragma unroll
    for (int i = 0; i < N; i++) asm volatile("" : "+f"(r[i])::"memory");
}
__device__ __forceinline__ void fence_async_smem() { asm volatile("fence.proxy.async.shared::cta;" ::: "memory"); }
__device__ __forceinline__ void bar_sync(int id, int n) { asm volatile("bar.sync %0, %1;" ::"r"(id), "r"(n) : "memory"); }
__device__ __forceinline__ void mbar_init(uint32_t a, uint32_t cnt) { asm volatile("mbarrier.init.shared::cta.b64 [%0], %1;" ::"r"(a), "r"(cnt) : "memory"); }
__device__ __forceinline__ void mbar_expect_tx(uint32_t a, uint32_t bytes) {
    asm volatile("mbarrier.arrive.expect_tx.shared::cta.b64 _, [%0], %1;" ::"r"(a), "r"(bytes) : "memory");
}
__device__ __forceinline__ void mbar_arrive(uint32_t a) { asm volatile("mbarrier.arrive.shared::cta.b64 _, [%0];" ::"r"(a) : "memory"); }
__device__ __forceinline__ uint32_t mapa(uint32_t a, uint32_t rank) {
    uint32_t r; asm("mapa.shared::cluster.u32 %0, %1, %2;" : "=r"(r) : "r"(a), "r"(rank)); return r;
}
__device__ __forceinline__ void mbar_wait(uint32_t a, uint32_t parity) {
    asm volatile("{\n.reg .pred p;\n.reg .u32 t0, t;\n"
                 "mbarrier.try_wait.parity.shared::cta.b64 p, [%0], %1, 0x989680;\n@p bra.uni WD;\n"
                 "mov.u32 t0, %%globaltimer_lo;\n"
                 "WL:\nmbarrier.try_wait.parity.shared::cta.b64 p, [%0], %1, 0x989680;\n@p bra.uni WD;\n"
                 "mov.u32 t, %%globaltimer_lo;\nsub.u32 t, t, t0;\nsetp.lt.u32 p, t, 2000000000;\n@p bra.uni WL;\ntrap;\nWD:\n}\n"
                 ::"r"(a), "r"(parity) : "memory");
}
__device__ __forceinline__ void tma2d(uint32_t dst, const CUtensorMap* tm, int c0, int c1, uint32_t bar) {
    asm volatile("cp.async.bulk.tensor.2d.shared::cluster.global.mbarrier::complete_tx::bytes [%0], [%1, {%3, %4}], [%2];"
                 ::"r"(dst), "l"(tm), "r"(bar), "r"(c0), "r"(c1) : "memory");
}
__device__ __forceinline__ void bulk_mc(uint32_t dst, const void* src, uint32_t bytes, uint32_t bar) {
    asm volatile("cp.async.bulk.shared::cluster.global.mbarrier::complete_tx::bytes.multicast::cluster [%0], [%1], %2, [%3], %4;"
                 ::"r"(dst), "l"(src), "r"(bytes), "r"(bar), "h"((uint16_t)3) : "memory");
}
__device__ __forceinline__ void bulk_s2s(uint32_t dst_cluster, uint32_t src, uint32_t bytes, uint32_t bar_cluster) {
    asm volatile("cp.async.bulk.shared::cluster.shared::cta.mbarrier::complete_tx::bytes [%0], [%1], %2, [%3];"
                 ::"r"(dst_cluster), "r"(src), "r"(bytes), "r"(bar_cluster) : "memory");
}
__device__ __forceinline__ void bulk_g2s(uint32_t dst, const void* src, uint32_t bytes, uint32_t bar) {
    asm volatile("cp.async.bulk.shared::cluster.global.mbarrier::complete_tx::bytes [%0], [%1], %2, [%3];"
                 ::"r"(dst), "l"(src), "r"(bytes), "r"(bar) : "memory");
}
__device__ __forceinline__ void bulk_s2g(void* dst, uint32_t src, uint32_t bytes) {
    asm volatile("cp.async.bulk.global.shared::cta.bulk_group [%0], [%1], %2;" ::"l"(dst), "r"(src), "r"(bytes) : "memory");
}
__device__ __forceinline__ void release2(uint32_t a, uint32_t b, uint32_t cnt, bool pred) {
    asm volatile("{\n.reg .pred p;\nsetp.ne.u32 p, %3, 0;\n@p mbarrier.arrive.shared::cluster.b64 _, [%0], %2;\n"
                 "@p mbarrier.arrive.shared::cluster.b64 _, [%1], %2;\n}\n" ::"r"(a), "r"(b), "r"(cnt), "r"((uint32_t)pred) : "memory");
}
__device__ __forceinline__ void release_all(uint32_t a, uint32_t b) {
    asm volatile("mbarrier.arrive.shared::cluster.b64 _, [%0];\nmbarrier.arrive.shared::cluster.b64 _, [%1];" ::"r"(a), "r"(b) : "memory");
}
__device__ __forceinline__ void store_flush() {
    asm volatile("cp.async.bulk.commit_group;\ncp.async.bulk.wait_group 0;\n"
                 "fence.proxy.async.global;\n"
                 "fence.acq_rel.gpu;" ::: "memory");
}
__device__ __forceinline__ void poll_counter(const unsigned int* c, unsigned int target) {
    unsigned int v;
    int it = 0;
#pragma unroll 1
    do {
        asm volatile("ld.acquire.gpu.global.u32 %0, [%1];" : "=r"(v) : "l"(c) : "memory");
        if (v >= target) break;
        if (++it > (1 << 22)) __trap();
        __nanosleep(64);
    } while (true);
    asm volatile("fence.proxy.async.global;" ::: "memory");
}
__device__ __forceinline__ void reset_sync() {
#pragma unroll 1
    for (int i = 0; i < 40; i++) g_sync(i) = 0u;
    g_syn[0][1] = 0u; g_syn[0][2] = 0u;
}
__device__ __forceinline__ void cluster_arrive() { asm volatile("barrier.cluster.arrive.relaxed.aligned;" ::: "memory"); }
__device__ __forceinline__ void cluster_wait() { asm volatile("barrier.cluster.wait.aligned;" ::: "memory"); }
__device__ __forceinline__ void sts32(uint32_t a, uint32_t v) { asm volatile("st.shared.u32 [%0], %1;" ::"r"(a), "r"(v) : "memory"); }
__device__ __forceinline__ void sts16(uint32_t a, uint16_t v) { asm volatile("st.shared.u16 [%0], %1;" ::"r"(a), "h"(v) : "memory"); }
__device__ __forceinline__ void sts128(uint32_t a, uint32_t x, uint32_t y, uint32_t z, uint32_t w) {
    asm volatile("st.shared.v4.u32 [%0], {%1,%2,%3,%4};" ::"r"(a), "r"(x), "r"(y), "r"(z), "r"(w) : "memory");
}
__device__ __forceinline__ void stsm4(uint32_t a, uint32_t x, uint32_t y, uint32_t z, uint32_t w) {
    asm volatile("stmatrix.sync.aligned.m8n8.x4.shared.b16 [%0], {%1,%2,%3,%4};" ::"r"(a), "r"(x), "r"(y), "r"(z), "r"(w) : "memory");
}
__device__ __forceinline__ uint32_t lds32(uint32_t a) { uint32_t v; asm volatile("ld.shared.u32 %0, [%1];" : "=r"(v) : "r"(a) : "memory"); return v; }
__device__ __forceinline__ uint32_t lds32v(uint32_t a) { uint32_t v; asm volatile("ld.volatile.shared.u32 %0, [%1];" : "=r"(v) : "r"(a) : "memory"); return v; }
__device__ __forceinline__ uint32_t lds16(uint32_t a) { uint16_t v; asm volatile("ld.shared.u16 %0, [%1];" : "=h"(v) : "r"(a) : "memory"); return v; }
__device__ __forceinline__ float4 lds128f(uint32_t a) {
    float4 v; asm volatile("ld.shared.v4.f32 {%0,%1,%2,%3}, [%4];" : "=f"(v.x), "=f"(v.y), "=f"(v.z), "=f"(v.w) : "r"(a) : "memory"); return v;
}
__device__ __forceinline__ float ex2f(float x) { float y; asm("ex2.approx.ftz.f32 %0, %1;" : "=f"(y) : "f"(x)); return y; }
__device__ __forceinline__ uint32_t pack_bf16(float lo, float hi) { uint32_t r; asm("cvt.rn.bf16x2.f32 %0, %1, %2;" : "=r"(r) : "f"(hi), "f"(lo)); return r; }
__device__ __forceinline__ uint32_t hfma2(uint32_t a, uint32_t b, uint32_t c) { uint32_t r; asm("fma.rn.f16x2 %0, %1, %2, %3;" : "=r"(r) : "r"(a), "r"(b), "r"(c)); return r; }
__device__ __forceinline__ float bf_lo(uint32_t v) { return __uint_as_float(v << 16); }
__device__ __forceinline__ float bf_hi(uint32_t v) { return __uint_as_float(v & 0xFFFF0000u); }

__device__ __forceinline__ void wg_qk(float (&d)[32], const uint32_t (&a)[4], Desc b, int sc) {
    asm volatile("{\n.reg .pred p;\nsetp.ne.b32 p, %37, 0;\n"
        "wgmma.mma_async.sync.aligned.m64n64k16.f32.bf16.bf16 {%0,%1,%2,%3,%4,%5,%6,%7,%8,%9,%10,%11,%12,%13,%14,%15,%16,%17,%18,%19,%20,%21,%22,%23,%24,%25,%26,%27,%28,%29,%30,%31}, {%32,%33,%34,%35}, %36, p, 1, 1, 0;\n}\n"
        : "+f"(d[0]), "+f"(d[1]), "+f"(d[2]), "+f"(d[3]), "+f"(d[4]), "+f"(d[5]), "+f"(d[6]), "+f"(d[7]), "+f"(d[8]), "+f"(d[9]), "+f"(d[10]), "+f"(d[11]), "+f"(d[12]), "+f"(d[13]), "+f"(d[14]), "+f"(d[15]), "+f"(d[16]), "+f"(d[17]), "+f"(d[18]), "+f"(d[19]), "+f"(d[20]), "+f"(d[21]), "+f"(d[22]), "+f"(d[23]), "+f"(d[24]), "+f"(d[25]), "+f"(d[26]), "+f"(d[27]), "+f"(d[28]), "+f"(d[29]), "+f"(d[30]), "+f"(d[31])
        : "r"(a[0]), "r"(a[1]), "r"(a[2]), "r"(a[3]), "l"(b), "r"(sc));
}
__device__ __forceinline__ void wg_pv(float (&d)[16], const uint32_t (&a)[4], Desc b, int sc) {
    asm volatile("{\n.reg .pred p;\nsetp.ne.b32 p, %21, 0;\n"
        "wgmma.mma_async.sync.aligned.m64n32k16.f32.bf16.bf16 {%0,%1,%2,%3,%4,%5,%6,%7,%8,%9,%10,%11,%12,%13,%14,%15}, {%16,%17,%18,%19}, %20, p, 1, 1, 1;\n}\n"
        : "+f"(d[0]), "+f"(d[1]), "+f"(d[2]), "+f"(d[3]), "+f"(d[4]), "+f"(d[5]), "+f"(d[6]), "+f"(d[7]), "+f"(d[8]), "+f"(d[9]), "+f"(d[10]), "+f"(d[11]), "+f"(d[12]), "+f"(d[13]), "+f"(d[14]), "+f"(d[15])
        : "r"(a[0]), "r"(a[1]), "r"(a[2]), "r"(a[3]), "l"(b), "r"(sc));
}
__device__ __forceinline__ void wg_proj(float (&d)[64], Desc a, Desc b, int sc) {
    asm volatile("{\n.reg .pred p;\nsetp.ne.b32 p, %66, 0;\n"
        "wgmma.mma_async.sync.aligned.m64n128k16.f32.bf16.bf16 {%0,%1,%2,%3,%4,%5,%6,%7,%8,%9,%10,%11,%12,%13,%14,%15,%16,%17,%18,%19,%20,%21,%22,%23,%24,%25,%26,%27,%28,%29,%30,%31,%32,%33,%34,%35,%36,%37,%38,%39,%40,%41,%42,%43,%44,%45,%46,%47,%48,%49,%50,%51,%52,%53,%54,%55,%56,%57,%58,%59,%60,%61,%62,%63}, %64, %65, p, 1, 1, 0, 1;\n}\n"
        : "+f"(d[0]), "+f"(d[1]), "+f"(d[2]), "+f"(d[3]), "+f"(d[4]), "+f"(d[5]), "+f"(d[6]), "+f"(d[7]), "+f"(d[8]), "+f"(d[9]), "+f"(d[10]), "+f"(d[11]), "+f"(d[12]), "+f"(d[13]), "+f"(d[14]), "+f"(d[15]), "+f"(d[16]), "+f"(d[17]), "+f"(d[18]), "+f"(d[19]), "+f"(d[20]), "+f"(d[21]), "+f"(d[22]), "+f"(d[23]), "+f"(d[24]), "+f"(d[25]), "+f"(d[26]), "+f"(d[27]), "+f"(d[28]), "+f"(d[29]), "+f"(d[30]), "+f"(d[31]), "+f"(d[32]), "+f"(d[33]), "+f"(d[34]), "+f"(d[35]), "+f"(d[36]), "+f"(d[37]), "+f"(d[38]), "+f"(d[39]), "+f"(d[40]), "+f"(d[41]), "+f"(d[42]), "+f"(d[43]), "+f"(d[44]), "+f"(d[45]), "+f"(d[46]), "+f"(d[47]), "+f"(d[48]), "+f"(d[49]), "+f"(d[50]), "+f"(d[51]), "+f"(d[52]), "+f"(d[53]), "+f"(d[54]), "+f"(d[55]), "+f"(d[56]), "+f"(d[57]), "+f"(d[58]), "+f"(d[59]), "+f"(d[60]), "+f"(d[61]), "+f"(d[62]), "+f"(d[63])
        : "l"(a), "l"(b), "r"(sc));
}
__device__ __forceinline__ void wg_oproj(float (&d)[16], Desc a, Desc b, int sc) {
    asm volatile("{\n.reg .pred p;\nsetp.ne.b32 p, %18, 0;\n"
        "wgmma.mma_async.sync.aligned.m64n32k16.f32.bf16.bf16 {%0,%1,%2,%3,%4,%5,%6,%7,%8,%9,%10,%11,%12,%13,%14,%15}, %16, %17, p, 1, 1, 1, 0;\n}\n"
        : "+f"(d[0]), "+f"(d[1]), "+f"(d[2]), "+f"(d[3]), "+f"(d[4]), "+f"(d[5]), "+f"(d[6]), "+f"(d[7]), "+f"(d[8]), "+f"(d[9]), "+f"(d[10]), "+f"(d[11]), "+f"(d[12]), "+f"(d[13]), "+f"(d[14]), "+f"(d[15])
        : "l"(a), "l"(b), "r"(sc));
}
__device__ __forceinline__ void wg_conv(float (&d)[16], const uint32_t (&a)[4], Desc b, int sc) {
    asm volatile("{\n.reg .pred p;\nsetp.ne.b32 p, %21, 0;\n"
        "wgmma.mma_async.sync.aligned.m64n32k16.f32.bf16.bf16 {%0,%1,%2,%3,%4,%5,%6,%7,%8,%9,%10,%11,%12,%13,%14,%15}, {%16,%17,%18,%19}, %20, p, 1, 1, 0;\n}\n"
        : "+f"(d[0]), "+f"(d[1]), "+f"(d[2]), "+f"(d[3]), "+f"(d[4]), "+f"(d[5]), "+f"(d[6]), "+f"(d[7]), "+f"(d[8]), "+f"(d[9]), "+f"(d[10]), "+f"(d[11]), "+f"(d[12]), "+f"(d[13]), "+f"(d[14]), "+f"(d[15])
        : "r"(a[0]), "r"(a[1]), "r"(a[2]), "r"(a[3]), "l"(b), "r"(sc));
}

struct cpx { float r, i; };
__device__ __forceinline__ cpx cmul(cpx a, cpx b) { return {fmaf(a.r, b.r, -a.i * b.i), fmaf(a.r, b.i, a.i * b.r)}; }
__device__ __forceinline__ cpx csqr(cpx a) { return {fmaf(a.r, a.r, -a.i * a.i), (a.r + a.r) * a.i}; }
__device__ __forceinline__ cpx cexp_at(float zl, float zt, float p) {
    float mag = ex2f(zl * p);
    float t = zt * p;
    t = (t - rintf(t)) * 6.283185307179586f;
    return {mag * __cosf(t), mag * __sinf(t)};
}
struct h2c { __half2 r, i; };
__device__ __forceinline__ h2c hpack(cpx a, cpx b) { return {__floats2half2_rn(a.r, b.r), __floats2half2_rn(a.i, b.i)}; }
__device__ __forceinline__ h2c hmul(h2c a, __half2 e) {
    __half2 er = __low2half2(e), ei = __high2half2(e);
    h2c o;
    o.r = __hfma2(a.r, er, __hneg2(__hmul2(a.i, ei)));
    o.i = __hfma2(a.r, ei, __hmul2(a.i, er));
    return o;
}
__device__ __forceinline__ __half2 epack(cpx e) { return __floats2half2_rn(e.r, e.i); }
__device__ __forceinline__ uint32_t h2u(__half2 h) { return *reinterpret_cast<uint32_t*>(&h); }
__device__ __forceinline__ __half2 u2h(uint32_t u) { return *reinterpret_cast<__half2*>(&u); }

struct KgenAnchor { h2c x0, y0; __half2 e1, e2, e4, e16, e32, e64, e256, e512, e1024; };
__device__ __forceinline__ float kgen_anchor(float zr, float zi, cpx c, KgenAnchor& a) {
    const float zl = zr * 1.4426950408889634f, zt = zi * 0.15915494309189535f;
    const cpx e1 = cexp_at(zl, zt, 1.f), e64 = cexp_at(zl, zt, 64.f);
    const cpx e2 = csqr(e1), e4 = csqr(e2), e8 = csqr(e4), e16 = csqr(e8), e32 = csqr(e16);
    const cpx e128 = csqr(e64), e256 = csqr(e128), e512 = csqr(e256), e1024 = csqr(e512), e2048 = csqr(e1024);
    a.y0 = hpack({1.f, 0.f}, {e8.r, -e8.i});
    a.e16 = epack({e16.r, -e16.i}); a.e32 = epack({e32.r, -e32.i}); a.e64 = epack({e64.r, -e64.i});
    a.x0 = hpack(c, cmul(c, e128));
    a.e1 = epack(e1); a.e2 = epack(e2); a.e4 = epack(e4); a.e256 = epack(e256); a.e512 = epack(e512); a.e1024 = epack(e1024);
    return fmaf(c.r, e2048.r, -c.i * e2048.i);
}
__device__ __forceinline__ void ldsm4t(uint32_t (&r)[4], uint32_t a) {
    asm volatile("ldmatrix.sync.aligned.m8n8.x4.trans.shared.b16 {%0,%1,%2,%3}, [%4];" : "=r"(r[0]), "=r"(r[1]), "=r"(r[2]), "=r"(r[3]) : "r"(a) : "memory");
}
__device__ __forceinline__ void kgen_put(uint32_t a, const h2c (&c)[4]) {
    sts128(a, h2u(c[0].r), h2u(c[1].r), h2u(c[2].r), h2u(c[3].r));
    sts128(a + 512, h2u(c[0].i), h2u(c[1].i), h2u(c[2].i), h2u(c[3].i));
}
struct Frag { uint32_t r[4], i[4]; };
__device__ __forceinline__ void frag_load(Frag& f, uint32_t a) { ldsm4t(f.r, a); ldsm4t(f.i, a + 512); }
__device__ __forceinline__ void frag_mul(Frag& o, const Frag& f, uint32_t ma) {
    uint4 er, ei;
    asm volatile("ld.shared.v4.u32 {%0,%1,%2,%3}, [%4];" : "=r"(er.x), "=r"(er.y), "=r"(er.z), "=r"(er.w) : "r"(ma) : "memory");
    asm volatile("ld.shared.v4.u32 {%0,%1,%2,%3}, [%4];" : "=r"(ei.x), "=r"(ei.y), "=r"(ei.z), "=r"(ei.w) : "r"(ma + 64) : "memory");
    const uint32_t a[4] = {er.x, er.y, er.z, er.w}, b[4] = {ei.x, ei.y, ei.z, ei.w};
#pragma unroll
    for (int j = 0; j < 4; j++) {
        const __half2 fr = u2h(f.r[j]), fi = u2h(f.i[j]), mr = u2h(a[j]), mi = u2h(b[j]);
        o.r[j] = h2u(__hfma2(fr, mr, __hneg2(__hmul2(fi, mi))));
        o.i[j] = h2u(__hfma2(fr, mi, __hmul2(fi, mr)));
    }
}
__device__ __forceinline__ void kgen_tile(float (&acc)[4], const Frag& y0, const Frag& y1, const Frag& x) {
#pragma unroll
    for (int ks = 0; ks < 4; ks++) {
        const uint32_t *a0 = (ks < 2 ? y0.r : y0.i) + 2 * (ks & 1), *a1 = (ks < 2 ? y1.r : y1.i) + 2 * (ks & 1), *b = (ks < 2 ? x.r : x.i) + 2 * (ks & 1);
        asm volatile("mma.sync.aligned.m16n8k16.row.col.f32.f16.f16.f32 {%0,%1,%2,%3}, {%4,%5,%6,%7}, {%8,%9}, {%0,%1,%2,%3};"
                     : "+f"(acc[0]), "+f"(acc[1]), "+f"(acc[2]), "+f"(acc[3])
                     : "r"(a0[0]), "r"(a1[0]), "r"(a0[1]), "r"(a1[1]), "r"(b[0]), "r"(b[1]));
    }
}
__device__ __forceinline__ void kgen_slice(const KgenAnchor& a, uint32_t W, int lane, float (&acc)[5][4]) {
    const uint32_t sa = W + lane * 16, ms = W + 4096 + ((lane >> 1) & 3) * 16 + (lane >> 3) * 4 + (lane & 1) * 2, ml = W + 4096 + (lane & 3) * 16;
    h2c c[4];
    sts16(ms, (uint16_t)(h2u(a.e64) & 0xFFFF));        sts16(ms + 64, (uint16_t)(h2u(a.e64) >> 16));
    sts16(ms + 128, (uint16_t)(h2u(a.e1) & 0xFFFF));   sts16(ms + 192, (uint16_t)(h2u(a.e1) >> 16));
    sts16(ms + 256, (uint16_t)(h2u(a.e256) & 0xFFFF)); sts16(ms + 320, (uint16_t)(h2u(a.e256) >> 16));
    c[0] = a.y0; c[1] = hmul(c[0], a.e16); c[2] = hmul(c[0], a.e32); c[3] = hmul(c[1], a.e32);
    kgen_put(sa, c);
    c[0] = a.x0; c[1] = hmul(c[0], a.e2); c[2] = hmul(c[0], a.e4); c[3] = hmul(c[1], a.e4);
    kgen_put(sa + 1024, c);
    __syncwarp();
    Frag y0, y1, x, x2;
    frag_load(y0, sa);
    frag_load(x, sa + 1024);
    c[0] = hmul(a.x0, a.e512); c[1] = hmul(c[0], a.e256); c[2] = hmul(c[0], a.e4); c[3] = hmul(c[1], a.e4);
    kgen_put(sa + 2048, c);
    c[0] = hmul(a.x0, a.e1024); c[1] = hmul(c[0], a.e256); c[2] = hmul(c[0], a.e512); c[3] = hmul(c[1], a.e512);
    kgen_put(sa + 3072, c);
    frag_mul(y1, y0, ml);
    kgen_tile(acc[0], y0, y1, x);
    frag_mul(x2, x, ml + 128);
    kgen_tile(acc[1], y0, y1, x2);
    frag_mul(x2, x, ml + 256);
    kgen_tile(acc[2], y0, y1, x2);
    __syncwarp();
    frag_load(x, sa + 2048);
    frag_load(x2, sa + 3072);
    kgen_tile(acc[3], y0, y1, x);
    kgen_tile(acc[4], y0, y1, x2);
    __syncwarp();
}
__device__ __forceinline__ int rowpos(int j, int r) {
    return j < 3 ? 128 * (r & 1) + (r & 6) + (j == 1) + (j == 2 ? 256 : 0) : j == 3 ? 512 + 128 * (r & 3) + (r & 4) : 1024 + 128 * r;
}
__device__ __forceinline__ uint32_t kp_off(uint32_t bits16) { return 2u * (uint32_t)max((int)bits16 - 0x3F7F, 0); }

struct SsmRegs { uint16_t lar[2], aim[2], cre[2], cim[2], ldt; };
__device__ __forceinline__ uint16_t ldraw(const __nv_bfloat16* p) { return __ldg((const uint16_t*)p); }
__device__ __forceinline__ float bf2f(uint16_t v) { return __uint_as_float((uint32_t)v << 16); }
__device__ __forceinline__ void ssm_load(const Params& P, int d, int tid, SsmRegs& s) {
#pragma unroll
    for (int i = 0; i < 2; i++) {
        int o = d * 256 + i * 128 + tid;
        s.lar[i] = ldraw(P.lar + o); s.aim[i] = ldraw(P.aim + o); s.cre[i] = ldraw(P.cre + o); s.cim[i] = ldraw(P.cim + o);
    }
    s.ldt = ldraw(P.ldt + d);
}

__device__ __forceinline__ void ssm_kgen(const SsmRegs& s, uint32_t R, int tid, int bar) {
    const uint32_t misc = R + R_MISC;
    const int lane = tid & 31, w = tid >> 5;
    const float dt = bf_lo(pack_bf16(expf(bf2f(s.ldt)), 0.f));
    const uint32_t cmw = __reduce_max_sync(~0u, max(max(s.cre[0] & 0x7FFFu, s.cim[0] & 0x7FFFu), max(s.cre[1] & 0x7FFFu, s.cim[1] & 0x7FFFu)));
    if (lane == 0) sts32(misc + w * 4, cmw << 16);
    TS(16);
    bar_sync(bar, 128);
    TS(17);
    float4 cm4 = lds128f(misc);
    const uint32_t cm = max(max(__float_as_uint(cm4.x), __float_as_uint(cm4.y)), max(__float_as_uint(cm4.z), __float_as_uint(cm4.w)));
    int ce = min(max((int)(cm >> 23), 20), 240);
    const float sc = __uint_as_float((uint32_t)(263 - ce) << 23);
    const float mult = 2.f * dt * __uint_as_float((uint32_t)(ce - 9) << 23);
    float acc[5][4] = {};
    const uint32_t W = R + w * 7168;
    KgenAnchor an, an1;
    float k2048 = kgen_anchor(-bf_lo(pack_bf16(expf(bf2f(s.lar[0])), 0.f)) * dt, bf2f(s.aim[0]) * dt, {bf2f(s.cre[0]) * sc, bf2f(s.cim[0]) * sc}, an)
                + kgen_anchor(-bf_lo(pack_bf16(expf(bf2f(s.lar[1])), 0.f)) * dt, bf2f(s.aim[1]) * dt, {bf2f(s.cre[1]) * sc, bf2f(s.cim[1]) * sc}, an1);
#pragma unroll
    for (int o = 16; o; o >>= 1) k2048 += __shfl_xor_sync(~0u, k2048, o);
    if (lane == 0) sts32(misc + 16 + w * 4, __float_as_uint(k2048));
#pragma unroll 1
    for (int sl = 0; sl < 2; sl++) {
        kgen_slice(an, W, lane, acc);
        an = an1;
        if (sl) TS(22); else TS(20);
    }
#pragma unroll
    for (int j = 0; j < 5; j++)
        sts128(W + 4096 + j * 512 + lane * 16, __float_as_uint(acc[j][0]), __float_as_uint(acc[j][1]), __float_as_uint(acc[j][2]), __float_as_uint(acc[j][3]));
    TS(13);
    bar_sync(bar, 128);
    TS(24);
#pragma unroll
    for (int h = 0; h < 2; h++) {
        const int j = h ? 4 : w, ln = h ? 8 * w + (lane & 7) : lane;
        const uint32_t a = R + 4096 + j * 512 + ln * 16;
        const float4 p0 = lds128f(a), p1 = lds128f(a + 7168), p2 = lds128f(a + 14336), p3 = lds128f(a + 21504);
        const int pa = rowpos(j, 2 * (ln & 3)) + 8 * (ln >> 2), pc = pa + 128;
        const uint32_t i0 = pack_bf16((float)pa, (float)pc), i1 = pack_bf16((float)(pa + 64), (float)(pc + 64));
        const uint32_t v0 = pack_bf16(((p0.x + p1.x) + (p2.x + p3.x)) * mult, ((p0.y + p1.y) + (p2.y + p3.y)) * mult);
        const uint32_t v1 = pack_bf16(((p0.z + p1.z) + (p2.z + p3.z)) * mult, ((p0.w + p1.w) + (p2.w + p3.w)) * mult);
        sts16(R + R_KP + kp_off(i0 & 0xFFFF), (uint16_t)(v0 & 0xFFFF)); sts16(R + R_KP + kp_off(i0 >> 16), (uint16_t)(v0 >> 16));
        sts16(R + R_KP + kp_off(i1 & 0xFFFF), (uint16_t)(v1 & 0xFFFF)); sts16(R + R_KP + kp_off(i1 >> 16), (uint16_t)(v1 >> 16));
    }
    if (tid == 127) {
        const float4 k4 = lds128f(misc + 16);
        sts16(R + R_KP + kp_off(0x4500), (uint16_t)(pack_bf16((k4.x + k4.y + k4.z + k4.w) * mult, 0.f) & 0xFFFF));
    }
    uint32_t ad[18];
    {
        const float f0 = (float)(2049 - 16 * tid);
#pragma unroll
        for (int q = 0; q < 18; q += 2) {
            const uint32_t pb = pack_bf16(f0 - (float)q, f0 - (float)(q + 1));
            ad[q] = R + R_KP + kp_off(pb & 0xFFFF); ad[q + 1] = R + R_KP + kp_off(pb >> 16);
        }
    }
    bar_sync(bar, 128);
    TS(25);
    {
        uint32_t v[18];
#pragma unroll
        for (int q = 0; q < 18; q++) v[q] = lds16(ad[q]);
        const uint32_t a0 = R + R_RV0 + tid * 32, a1 = R + R_RV1 + tid * 32;
#pragma unroll
        for (int h = 0; h < 2; h++) {
            const int q = 8 * h;
            sts128(a1 + 16 * h, v[q] | (v[q + 1] << 16), v[q + 2] | (v[q + 3] << 16), v[q + 4] | (v[q + 5] << 16), v[q + 6] | (v[q + 7] << 16));
            sts128(a0 + 16 * h, v[q + 1] | (v[q + 2] << 16), v[q + 3] | (v[q + 4] << 16), v[q + 5] | (v[q + 6] << 16), v[q + 7] | (v[q + 8] << 16));
        }
        if (tid == 127) {
            sts128(a1 + 32, v[16] | (v[17] << 16), 0, 0, 0); sts128(a1 + 48, 0, 0, 0, 0);
            sts128(a0 + 32, v[17], 0, 0, 0); sts128(a0 + 48, 0, 0, 0, 0);
        }
    }
}

template <int A> __device__ __forceinline__ void conv_mma(float (&acc)[4][16], const uint32_t (&a)[4], Desc db) {
#pragma unroll
    for (int G = A; G < 4; G++) wg_conv(acc[G], a, db + 32 * (G - A), 1);
}
__device__ __forceinline__ void conv_ldA(uint32_t (&a)[4], uint32_t f) {
    a[0] = lds32v(f); a[1] = lds32v(f - 16); a[2] = lds32v(f + 16); a[3] = lds32v(f);
}
__device__ __forceinline__ void ssm_conv(float (&acc)[4][16], uint32_t R, uint32_t U, int tid, int bar) {
    const int lane = tid & 31, w = tid >> 5, g = lane >> 2, t = lane & 3;
    uint32_t a0[4], a1[4], a2[4], a3[4];
    uint32_t fb = ((g & 1) ? R + R_RV1 + 2 * (2049 - g + 2 * t) : R + R_RV0 + 2 * (2048 - g + 2 * t)) - 256 * w;
    Desc db = make_desc(U + 128, U_HS, 128, 0);
#pragma unroll 1
    for (int eps = 0; eps < 8; eps++) {
        conv_ldA(a0, fb); conv_ldA(a3, fb - 3072);
        wg_fence();
        conv_mma<0>(acc, a0, db);
        conv_mma<3>(acc, a3, db);
        wg_commit();
        wg_wait<1>();
        conv_ldA(a1, fb - 1024); conv_ldA(a2, fb - 2048);
        wg_fence();
        conv_mma<1>(acc, a1, db);
        conv_mma<2>(acc, a2, db);
        wg_commit();
        wg_wait<1>();
        fb -= 32; db -= 1;
    }
    wg_wait<0>();
    fence_regs(acc[0]); fence_regs(acc[1]); fence_regs(acc[2]); fence_regs(acc[3]);
    TS(11);
    bar_sync(bar, 128);
    const uint32_t pa = R + ((w * (33 - w)) >> 1) * 512 + lane * 16;
#pragma unroll
    for (int b = 0; b < 16; b++)
        if (b < 13 || b + w < 16)
            sts128(pa + b * 512, __float_as_uint(acc[b >> 2][4 * (b & 3)]), __float_as_uint(acc[b >> 2][4 * (b & 3) + 1]),
                   __float_as_uint(acc[b >> 2][4 * (b & 3) + 2]), __float_as_uint(acc[b >> 2][4 * (b & 3) + 3]));
}
__device__ __forceinline__ void ssm_finish(uint32_t R, uint32_t d2, int lane, int J0, int step) {
#pragma unroll 1
    for (int J = J0; J < 16; J += step) {
        const uint32_t ua = R + R_U + 128 + ((lane >> 3) & 1) * U_HS + (8 * J + (lane & 7)) * 16, pa = R + J * 512 + lane * 16;
        uint32_t u0, u1;
        asm volatile("ldmatrix.sync.aligned.m8n8.x2.trans.shared.b16 {%0,%1}, [%2];" : "=r"(u0), "=r"(u1) : "r"(ua) : "memory");
        const float4 z = make_float4(0.f, 0.f, 0.f, 0.f);
        const float4 p0 = lds128f(pa), p1 = J >= 1 ? lds128f(pa + 15 * 512) : z, p2 = J >= 2 ? lds128f(pa + 29 * 512) : z, p3 = J >= 3 ? lds128f(pa + 42 * 512) : z;
        asm("mul.rn.bf16x2 %0, %0, %1;" : "+r"(u0) : "r"(d2));
        asm("mul.rn.bf16x2 %0, %0, %1;" : "+r"(u1) : "r"(d2));
        asm("add.rn.bf16x2 %0, %1, %0;" : "+r"(u0) : "r"(pack_bf16((p0.x + p1.x) + (p2.x + p3.x), (p0.y + p1.y) + (p2.y + p3.y))));
        asm("add.rn.bf16x2 %0, %1, %0;" : "+r"(u1) : "r"(pack_bf16((p0.z + p1.z) + (p2.z + p3.z), (p0.w + p1.w) + (p2.w + p3.w))));
        asm volatile("stmatrix.sync.aligned.m8n8.x2.trans.shared.b16 [%0], {%1,%2};" ::"r"(ua), "r"(u0), "r"(u1) : "memory");
    }
}

struct ExpC { uint32_t one, c3; };
__device__ __forceinline__ uint32_t ex2_pair(float lo, float hi, const ExpC& c) {
    uint32_t w; asm("cvt.pack.sat.u16.s32 %0, %1, %2;" : "=r"(w) : "r"(__float_as_int(hi)), "r"(__float_as_int(lo)));
    uint32_t m; asm("lop3.b32 %0, %1, 0x03FF03FF, %2, 0xEA;" : "=r"(m) : "r"(w), "r"(c.one));
    uint32_t q = hfma2(c.c3, m, 0x9EEC9EECu);
    q = hfma2(q, m, 0x379E379Eu);
    q = hfma2(q, m, 0x483A483Au);
    return ((w & 0xFC00FC00u) >> 3) + q;
}
template <uint32_t MASK, int Q0, int Q1>
__device__ __forceinline__ void exp_quads(const float (&s)[32], uint32_t (&p0)[4], uint32_t (&p)[4][4], const ExpC& c) {
#pragma unroll
    for (int i = 8 * Q0; i < 8 * Q1; i += 2) {
        const uint32_t r = ((MASK >> (i / 4)) & 1) ? ex2_pair(s[i], s[i + 1], c) : pack_bf16(ex2f(s[i]), ex2f(s[i + 1]));
        if (i < 8) p0[i / 2] = r; else p[i / 8][(i % 8) / 2] = r;
    }
}
__device__ __forceinline__ void pv_block(float (&o)[16], uint32_t (&p0)[4], uint32_t (&p)[4][4], Desc dv) {
    wg_pv(o, p0, dv, 1);
#pragma unroll
    for (int kk = 1; kk < 4; kk++) wg_pv(o, p[kk], dv + kk * 16, 1);
}

__device__ __forceinline__ float fb_score(const uint32_t* q, int j) {
    const uint8_t* base = g_kv + (j >> 6) * 8192 + (j & 63) * 16;
    const float ks = ((POLY_MASK >> ((j >> 3) & 15)) & 1) ? 0x1p79f : 0x1p-60f;
    float s = 0.f;
#pragma unroll 2
    for (int c = 0; c < DH / 2; c++) {
        const uint32_t kk = __ldcg((const uint32_t*)(base + (c >> 2) * 1024 + (c & 3) * 4)), qq = __ldcg(q + c);
        s = fmaf(bf_lo(qq) * 0x1p60f, bf_lo(kk) * ks, s);
        s = fmaf(bf_hi(qq) * 0x1p60f, bf_hi(kk) * ks, s);
    }
    return s;
}
__device__ __noinline__ void attn_fallback(uint32_t omat, int pos0, int h, int grp0, int lane) {
#pragma unroll 1
    for (int r = 0; r < 16; r++) {
        const uint32_t* q = (const uint32_t*)(g_q + (size_t)(pos0 + r) * QP + h * DH);
        float m = -INFINITY;
#pragma unroll 1
        for (int j = lane; j < SEQ; j += 32) m = fmaxf(m, fb_score(q, j));
#pragma unroll
        for (int s = 16; s; s >>= 1) m = fmaxf(m, __shfl_xor_sync(~0u, m, s));
        float o = 0.f;
#pragma unroll 1
        for (int j0 = 0; j0 < SEQ; j0 += 32) {
            const float p = exp2f(fb_score(q, j0 + lane) - m);
            const uint16_t* vb = (const uint16_t*)(g_kv + (j0 >> 6) * 8192 + 4096 + (lane >> 3) * 1024 + (j0 & 63) * 16) + (lane & 7);
#pragma unroll 4
            for (int j = 0; j < 32; j++) o = fmaf(__shfl_sync(~0u, p, j), __uint_as_float((uint32_t)__ldcg(vb + 8 * j) << 16), o);
        }
        const float l = __shfl_sync(~0u, o, DH);
        if (lane < DH) {
            const int k = h * DH + lane;
            sts16(omat + (grp0 + (r >> 3)) * 7168 + (k >> 3) * 128 + (r & 7) * 16 + (k & 7) * 2, (uint16_t)(pack_bf16(o / l, 0.f) & 0xFFFF));
        }
    }
}

__device__ __forceinline__ uint32_t wo_box(int w, int kc, int& late) {
    late = -1;
    if (w < 3) {
        const int idx = kc * 3 + w;
        if (idx < 15) return OFF_W + idx * 8192;
        late = (idx - 15) >> 1;
        return OFF_RING + (idx - 15) * 8192;
    }
    if (kc == 0) return OFF_W + 15 * 8192;
    if (kc == 1) return OFF_O + 28672;
    if (kc == 2) return OFF_O + 32768;
    late = 3;
    return OFF_RING + 3 * SLOT + (kc - 3) * 4096;
}
__device__ __forceinline__ void wo_issue(const Params& P, uint32_t sb, int rank, int w, int kc, uint32_t bar) {
    int late;
    uint32_t a = sb + wo_box(w, kc, late);
    tma2d(a, w < 3 ? &P.tm_wo64 : &P.tm_wo32, 224 * rank + 64 * w, 64 * kc, bar);
}

__global__ void __cluster_dims__(2, 1, 1) __launch_bounds__(NTHR, 1) fused_kernel(const __grid_constant__ Params P) {
    extern __shared__ __align__(1024) uint8_t smem[];
    const uint32_t sb = smem_u32(smem);
    const int wg = __reduce_max_sync(~0u, threadIdx.x >> 7);
    const int cta = blockIdx.x, rank = cta & 1, cl = cta >> 1;
    const uint32_t bars = sb + OFF_BAR;
    const bool xtra = cta >= NMAIN;
    const bool gemm = rank == 0 && !xtra;
    const int pb = cl >> 2, pq = cl & 3;
    const bool kvw = gemm && pq == 0;
    const int ch0 = xtra ? 256 + 48 * (cta - NMAIN) : gemm ? 255 + 3 * cl : 4 * cl, chs = xtra ? 12 : 1;
    const int k0 = kvw ? 2 : gemm ? 1 : 0;
    const int nst = pq ? 5 : 6, stsz = pq ? 24576 : 16384;
    const uint32_t stbase = sb + (pq ? OFF_B0 : OFF_B0 + 57344);
    TS(0);
    if (threadIdx.x < 64 && (threadIdx.x & 31) == 0)
        asm volatile("prefetch.tensormap [%0];" ::"l"(gemm ? (threadIdx.x ? &P.tm_wq : &P.tm_x) : (threadIdx.x ? &P.tm_ut : &P.tm_u)) : "memory");
    auto load_step = [&](int n, int stage) {
        const uint32_t st = stbase + stage * stsz, fb = bars + 8 * (B_G + stage + (stage > 2));
        const int mh = pq ? n >= 7 : n & 1, k = pq ? n - 7 * mh : n >> 1;
        mbar_expect_tx(fb, stsz);
        tma2d(st, &P.tm_x, 64 * k, 128 * pb + 64 * mh, fb);
        tma2d(st + stsz - 8192, &P.tm_wq, 128 * pq, 64 * k, fb);
        if (pq) tma2d(st + 8192, &P.tm_wq, 128 * pq - 64, 64 * k, fb);
    };
    const uint32_t peer_bars = __reduce_max_sync(~0u, mapa(bars, rank ^ 1));
    auto publish = [&](int p) {
        const uint32_t stg = stbase + ((pq ? 7 * p + 6 : 12 + p) % nst) * stsz;
        if (pq == 0) {
            bulk_s2g(g_kv + pb * SLOT + p * 8192, stg, 8192);
#pragma unroll
            for (int m = 0; m < 2; m++) {
                const float4 r4 = lds128f(sb + OFF_MISC + 32 * p + 16 * m);
                asm volatile("red.relaxed.gpu.global.max.u32 [%0], %1;" ::"l"(&g_syn[0][1 + m]),
                             "r"(max(max(__float_as_uint(r4.x), __float_as_uint(r4.y)), max(__float_as_uint(r4.z), __float_as_uint(r4.w)))) : "memory");
            }
        } else asm volatile("cp.async.bulk.tensor.2d.global.shared::cta.bulk_group [%0, {%2, %3}], [%1];"
                            ::"l"(&P.tm_q), "r"(stg), "r"(128 * pq - 64), "r"(128 * pb + 64 * p) : "memory");
        asm volatile("cp.async.bulk.tensor.2d.global.shared::cta.bulk_group [%0, {%2, %3}], [%1];"
                     ::"l"(&P.tm_q), "r"(stg + 8192), "r"(128 * pq), "r"(128 * pb + 64 * p) : "memory");
        asm volatile("cp.async.bulk.commit_group;\ncp.async.bulk.wait_group.read 0;" ::: "memory");
        if (pq && p == 0) asm volatile("mbarrier.arrive.shared::cta.b64 _, [%0], 128;" ::"r"(bars + 8 * (B_GD + 1)) : "memory");
        release2(bars + 8 * B_UALL, peer_bars + 8 * B_UALL, 2, true);
        store_flush();
        asm volatile("red.relaxed.gpu.global.add.u32 [%0], 1;" ::"l"(&g_sync(8 + 2 * pb + p)) : "memory");
        if (pq == 0) asm volatile("red.relaxed.gpu.global.add.u32 [%0], 1;" ::"l"(&g_sync(0)) : "memory");
    };

    if (wg == 4) {
        asm volatile("setmaxnreg.dec.sync.aligned.u32 32;");
        const int lane = threadIdx.x & 31, w = (threadIdx.x >> 5) & 3, uw = __reduce_max_sync(~0u, w);
        if (lane == 0) {
            const unsigned long long tb = uw == 0 ? BARCNT0 : uw == 1 ? BARCNT1 : uw == 2 ? BARCNT2 : BARCNT3;
#pragma unroll
            for (int i = 0; i < 10; i++) mbar_init(bars + 8 * (uw + 4 * i), 1u << ((tb >> (4 * i)) & 15));
            asm volatile("fence.mbarrier_init.release.cluster;" ::: "memory");
            fence_async_smem();
        }
        __syncwarp();
#pragma unroll
        for (int k = 0; k < 4; k++) asm volatile("bar.arrive %0, 256;" ::"r"(8 + k) : "memory");
        if (lane == 0) {
            if (gemm && w < 3) {
                load_step(w, w);
                if (w + 3 < nst) load_step(w + 3, w + 3);
            } else if (gemm) {
                if (pq == 0) {
                    mbar_expect_tx(bars + 8 * B_WKV, 2 * 25088);
#pragma unroll 1
                    for (int i = 0; i < 4; i++)
                        bulk_g2s(sb + OFF_B0 + (i >> 1) * 28672 + (i & 1) * 12544, ((i & 1) ? P.wv : P.wk) + (i >> 1) * 6272, 12544, bars + 8 * B_WKV);
                }
            } else if (!xtra) {
#pragma unroll 1
                for (int i = w; i < 7; i += 4) {
                    mbar_expect_tx(bars + 8 * i, 4096);
                    tma2d(sb + OFF_RING + i * 4096, &P.tm_u, 64 * i, 32 * cl, bars + 8 * i);
                }
            }
        }
        __syncwarp();
        bar_sync(7, 128);
        TH(0);
        cluster_arrive();
        if (!gemm && !xtra) {
            const uint32_t dst = sb + OFF_RING + 32768 + (lane & 7) * 64 + ((lane >> 3) & 1) * 32 + ((((lane >> 4) ^ (lane >> 1)) & 1) << 4);
#pragma unroll 1
            for (int bx = w; bx < 7; bx += 4) {
                mbar_wait(bars + 8 * bx, 0);
                TH(1);
#pragma unroll 1
                for (int i = 0; i < 2; i++) {
                    uint32_t r[4][4];
#pragma unroll
                    for (int j = 0; j < 4; j++)
                        asm volatile("ldmatrix.sync.aligned.m8n8.x4.shared.b16 {%0,%1,%2,%3}, [%4];" : "=r"(r[j][0]), "=r"(r[j][1]), "=r"(r[j][2]), "=r"(r[j][3])
                                     : "r"(sb + OFF_RING + bx * 4096 + lane * 128 + ((((4 * i + j) ^ lane) & 7) << 4)) : "memory");
#pragma unroll
                    for (int j = 0; j < 4; j++)
                        asm volatile("stmatrix.sync.aligned.m8n8.x4.trans.shared.b16 [%0], {%1,%2,%3,%4};" ::"r"(dst + bx * 4096 + (4 * i + j) * 512),
                                     "r"(r[j][0]), "r"(r[j][1]), "r"(r[j][2]), "r"(r[j][3]) : "memory");
                }
                fence_async_smem();
                __syncwarp();
                if (lane == 0) {
                    asm volatile("cp.async.bulk.tensor.2d.global.shared::cta.bulk_group [%0, {%2, %3}], [%1];"
                                 ::"l"(&P.tm_ut), "r"(sb + OFF_RING + 32768 + bx * 4096), "r"(64 + 16 * cl), "r"(128 * bx) : "memory");
                    store_flush();
                    asm volatile("red.relaxed.gpu.global.add.u32 [%0], 1;" ::"l"(&g_sync(bx < 4 ? 3 + bx + (bx > 0) : 2)) : "memory");
                }
                __syncwarp();
                if (bx < 4) TH(2); else TH(3);
            }
        }
        cluster_wait();
        release2(bars + 8 * B_UALL, peer_bars + 8 * B_UALL, 1, lane == 0 && !gemm && !xtra);
        if (w == 0) {
            if (lane == 0 && gemm) {
#pragma unroll 1
                for (int n = nst, stage = 0, par = 0; n < 14; n++) {
                    mbar_wait(bars + 8 * (B_GD + stage), par);
                    load_step(n, stage);
                    if (++stage == nst) { stage = 0; par ^= 1; }
                }
            }
            __syncwarp();
            if (lane == 0 && !xtra) {
#pragma unroll 1
                for (int i = 0; i < 4; i++) mbar_expect_tx(bars + 8 * (B_KFULL + i), SLOT);
                mbar_wait(bars + 8 * B_UALL, 0);
                {
                    uint32_t c, km, vm;
                    int it = 0;
#pragma unroll 1
                    do {
                        asm volatile("{\n.reg .u32 x;\nld.acquire.gpu.global.v4.u32 {%0,%1,%2,x}, [%3];\n}\n" : "=r"(c), "=r"(km), "=r"(vm) : "l"(&g_sync(0)) : "memory");
                        if (c >= 32) break;
                        if (++it > (1 << 22)) __trap();
                        __nanosleep(64);
                    } while (true);
                    asm volatile("fence.proxy.async.global;" ::: "memory");
                    bulk_mc(sb + OFF_RING + rank * 8192, g_kv + (cl & 15) * SLOT + rank * 8192, 8192, bars + 8 * B_KFULL);
                    sts32(sb + OFF_MISC - 16, km); sts32(sb + OFF_MISC - 12, vm);
                    mbar_arrive(bars + 8 * B_KN);
                }
                TH(7);
                TH(8);
#pragma unroll 1
                for (int i = 1; i < 20; i++) {
                    const int s = i & 3;
                    const uint32_t fb = bars + 8 * (B_KFULL + s), dst = sb + OFF_RING + s * SLOT;
                    if (i >= 4) {
                        mbar_wait(bars + 8 * (B_KEMPTY + s), ((i >> 2) - (s != 3)) & 1);
                        mbar_expect_tx(fb, SLOT);
                    }
                    if (i < 16) {
                        bulk_mc(dst + rank * 8192, g_kv + ((i + cl) & 15) * SLOT + rank * 8192, 8192, fb);
                    } else {
#pragma unroll 1
                        for (int j = 0; j < (s < 3 ? 2 : 4); j++) {
                            const int idx = 15 + 2 * s + j;
                            wo_issue(P, sb, rank, s < 3 ? idx % 3 : 3, s < 3 ? idx / 3 : 3 + j, fb);
                        }
                    }
                }
            }
        } else if (w == 1) {
            if (lane < 10) asm volatile("prefetch.tensormap [%0];" ::"l"(&P.tm_x + lane) : "memory");
            __syncwarp();
            if (lane == 0) {
                if (gemm) {
                    if (pq) {
                        mbar_wait(bars + 8 * B_STG, 0);
                        publish(0);
                    }
                }
                TH(4);
            }
            __syncwarp();
            TH(7);
            bar_sync(13, 96);
            if (lane == 0) {
#pragma unroll 1
                for (int r = k0; r < 4; r++) bulk_s2g(g_y + (size_t)(ch0 + chs * r) * 2176, sb + OFF_S + r * SREG + R_U, 4352);
                store_flush();
                asm volatile("red.relaxed.gpu.global.add.u32 [%0], 1;" ::"l"(&g_sync(1)) : "memory");
                mbar_arrive(bars + 8 * B_YFREE);
                if (!xtra) mbar_wait(bars + 8 * B_QDONE, 0);
#pragma unroll 1
                for (int idx = 0; idx < (xtra ? 0 : 18); idx++) {
                    wo_issue(P, sb, rank, idx < 15 ? idx % 3 : 3, idx < 15 ? idx / 3 : idx - 15, bars + 8 * B_WO);
                }
            }
        } else {
            const int hw = w - 2;
            if (lane == 0) {
                if (hw) {
                    mbar_expect_tx(bars + 8 * B_U, (2 - k0) * 4352);
                    mbar_expect_tx(bars + 8 * (B_U + 1), 2 * 4352);
                    TH(5);
                    poll_counter(&g_sync((gemm || xtra) ? 2 : 3 + (cl >> 4) + (cl >= 16)), (gemm || xtra) ? 192 : 64);
                    TH(6);
#pragma unroll 1
                    for (int r = k0; r < 4; r++)
                        bulk_g2s(sb + OFF_S + r * SREG + R_U, g_ut + (size_t)(ch0 + chs * r) * 2176, 4352, bars + 8 * (B_U + (r >> 1)));
                }
                mbar_expect_tx(bars + 8 * (B_OFULL + 2 * hw), 3584);
                mbar_expect_tx(bars + 8 * (B_OFULL + 2 * hw + 1), 3584);
                mbar_expect_tx(bars + 8 * (hw ? B_WO : B_READY), hw ? 15 * 8192 + 3 * 4096 : 32 * QP);
                if (hw == 0 && !xtra) {
                    if (gemm) mbar_wait(bars + 8 * B_UALL, 0);
                    poll_counter(&g_sync(8 + (cta >> 2)), 4);
                    TH(8);
                    bulk_g2s(sb + OFF_W, g_q + (size_t)(16 * cta) * QP, 32 * QP, bars + 8 * B_READY);
                }
            }
            __syncwarp();
            mbar_wait(bars + 8 * B_RFREE, 0);
#pragma unroll 1
            for (int k = k0; k < 4; k++) {
                const uint32_t dv = ldraw(P.dsk + ch0 + chs * k);
                ssm_finish(sb + OFF_S + k * SREG, dv | (dv << 16), lane, hw, 2);
            }
            fence_async_smem();
            asm volatile("bar.arrive 13, 96;" ::: "memory");
            if (!xtra) {
            const uint32_t st = sb + OFF_O + rank * 14336 + hw * 7168;
            if (lane == 0) {
                mbar_wait(bars + 8 * B_YFREE, 0);
                poll_counter(&g_sync(1), NCTA);
                mbar_expect_tx(bars + 8 * (B_Y + hw), 7168);
                tma2d(st, &P.tm_y, 64 + 8 * cta, 448 * hw, bars + 8 * (B_Y + hw));
                tma2d(st + 3584, &P.tm_y, 64 + 8 * cta, 448 * hw + 224, bars + 8 * (B_Y + hw));
            }
            __syncwarp();
            mbar_wait(bars + 8 * (B_Y + hw), 0);
            const int rho = lane & 7, mi = lane >> 3;
            const uint32_t src = st + (8 * (rho >> 1) + 2 * mi + (rho & 1)) * 32;
            __nv_bfloat16* dst = P.out + (size_t)(16 * cta + (lane >> 2)) * (2 * DM) + DM + 224 * hw + 8 * (lane & 3);
#pragma unroll 1
            for (int it = 0; it < 14; it++) {
                uint4 v;
                asm volatile("ldmatrix.sync.aligned.m8n8.x4.trans.shared.b16 {%0,%1,%2,%3}, [%4];"
                             : "=r"(v.x), "=r"(v.y), "=r"(v.z), "=r"(v.w) : "r"(src + (it >> 1) * 1024 + (it & 1) * 16) : "memory");
                *(uint4*)(dst + (size_t)(it & 1) * 8 * (2 * DM) + 32 * (it >> 1)) = v;
            }
            __syncwarp();
            if (lane == 0) mbar_arrive(bars + 8 * B_YDONE);
            }
        }
        __syncwarp();
        TH(11);
        if (lane == 0 && atomicAdd(&g_sync(4), 1u) == 4 * NCTA - 1) reset_sync();
        if (xtra) return;
        cluster_arrive();
        cluster_wait();
        return;
    }

    const int tid = threadIdx.x & 127;
    SsmRegs sp;
    ssm_load(P, ch0 + chs * wg, tid, sp);
    cluster_arrive();
    asm volatile("setmaxnreg.inc.sync.aligned.u32 112;");
    const int lane = tid & 31, w = tid >> 5, g = lane >> 2, t = lane & 3;
    if (wg < k0) {
        bar_sync(8 + wg, 256);
        if (kvw) {
            TS(24);
            mbar_wait(bars + 8 * B_WKV, 0);
            TS(25);
            {
                const int hf = wg;
                uint2 v[2][14];
                const uint32_t base = sb + OFF_B0 + hf * 28672;
#pragma unroll
                for (int j = 0; j < 2; j++)
#pragma unroll
                    for (int c = 0; c < 14; c++)
                        asm volatile("ld.shared.v2.u32 {%0,%1}, [%2];" : "=r"(v[j][c].x), "=r"(v[j][c].y)
                                     : "r"(base + (c >= 7 ? 12544 - 56 : 0) + min(tid + 128 * j, 223) * 56 + c * 8) : "memory");
                bar_sync(1 + wg, 128);
#pragma unroll
                for (int j = 0; j < 2; j++) {
                    const int k = min(tid + 128 * j, 223);
                    const uint32_t row = base + k * 128, x = (k & 7) << 4;
#pragma unroll
                    for (int m = 0; m < 2; m++) {
#pragma unroll
                        for (int c = 0; c < 3; c++) sts128(row + ((64 * m + 16 * c) ^ x), v[j][7 * m + 2 * c].x, v[j][7 * m + 2 * c].y, v[j][7 * m + 2 * c + 1].x, v[j][7 * m + 2 * c + 1].y);
                        sts128(row + ((64 * m + 48) ^ x), v[j][7 * m + 6].x, v[j][7 * m + 6].y, 0, 0);
                    }
                }
            }
            TS(26);
            fence_async_smem();
            bar_sync(6, 256);
            TS(27);
        }
        int stage = wg, par = 0;
#pragma unroll 1
        for (int mh = wg; mh < 2; mh += k0) {
        float acc[64];
        zero_regs(acc);
        int prev = 0;
#pragma unroll 1
        for (int kc = 0; kc < 7; kc++) {
            mbar_wait(bars + 8 * (B_G + stage + (stage > 2)), par);
            if (kc == 0 && mh == 0) TS(28);
            const uint32_t st = stbase + stage * stsz, b0 = kvw ? sb + OFF_B0 + kc * 8192 : st + 8192;
            const Desc da = make_desc(st, 16, 1024, 1);
            const Desc db = make_desc(b0, st + stsz - 8192 - b0, 1024, 1);
            wg_fence();
#pragma unroll
            for (int ks = 0; ks < 4; ks++) wg_proj(acc, da + ks * 2, db + ks * 128, 1);
            wg_commit();
            wg_wait<1>();
            if (kc > 0) mbar_arrive(bars + 8 * (B_GD + prev));
            if (kc == 1 && mh == 0) mbar_arrive(bars + 8 * B_GO);
            prev = stage;
            stage += k0;
            if (stage >= nst) { stage -= nst; par ^= 1; }
        }
        wg_wait<0>();
        fence_regs(acc);
        TS(14);
        bar_sync(1 + wg, 128);
        const uint32_t stg = stbase + prev * stsz;
        const float cq = 0.27264379719888306f * 0x1p-60f;
        const int r8 = lane & 7, rrow = 16 * w + (lane & 15), cb = lane >> 4;
#pragma unroll
        for (int jp = 0; jp < 8; jp++) {
            if (jp >= 4 || !kvw) {
                const float* a = &acc[8 * jp];
                stsm4(stg + (jp >> 2) * 8192 + rrow * 128 + (((2 * (jp & 3) + cb) ^ r8) << 4), pack_bf16(a[0] * cq, a[1] * cq), pack_bf16(a[2] * cq, a[3] * cq),
                      pack_bf16(a[4] * cq, a[5] * cq), pack_bf16(a[6] * cq, a[7] * cq));
            }
        }
        if (kvw) {
            uint32_t red[2];
#pragma unroll
            for (int m = 0; m < 2; m++) {
                uint32_t v[8], sc[2];
                float nrm[2] = {0.f, 0.f};
#pragma unroll
                for (int e = 0; e < 2; e++) sc[e] = ((POLY_MASK >> (8 * mh + 2 * w + e)) & 1) ? 0x18001800u : 0x5D805D80u;
#pragma unroll
                for (int i = 0; i < 8; i++) {
                    v[i] = pack_bf16(acc[16 * m + 2 * i], acc[16 * m + 2 * i + 1]);
                    nrm[i & 1] = fmaf(bf_lo(v[i]), bf_lo(v[i]), fmaf(bf_hi(v[i]), bf_hi(v[i]), nrm[i & 1]));
                    if (i >= 6 && t == 2) v[i] = (m == 0 && sc[i & 1] == 0x5D805D80u) ? 0x41903F80u : 0x00003F80u;
                    if (m == 0) asm("mul.rn.bf16x2 %0, %0, %1;" : "+r"(v[i]) : "r"(sc[i & 1]));
                }
                red[m] = 0;
#pragma unroll
                for (int e = 0; e < 2; e++) {
                    nrm[e] += __shfl_xor_sync(~0u, nrm[e], 1); nrm[e] += __shfl_xor_sync(~0u, nrm[e], 2);
                    red[m] = max(__float_as_uint(nrm[e]) & 0x7FFFFFFFu, red[m]);
                }
                red[m] = __reduce_max_sync(~0u, red[m]);
                if (lane == 0) sts32(sb + OFF_MISC + 32 * mh + 16 * m + 4 * w, red[m]);
                stsm4(stg + (4 * m + cb) * 1024 + rrow * 16, v[0], v[1], v[2], v[3]);
                stsm4(stg + (4 * m + 2 + cb) * 1024 + rrow * 16, v[4], v[5], v[6], v[7]);
            }
        }
        fence_async_smem();
        if (pq && mh == 0) mbar_arrive(bars + 8 * B_STG);
        else {
            cluster_wait();
            bar_sync(1 + wg, 128);
            if (tid == 0) publish(mh);
            __syncwarp();
        }
        TS(15);
        }
    } else {
        const uint32_t R = sb + OFF_S + wg * SREG;
        TS(10);
        if (gemm && wg >= 2) { bar_sync(8 + wg, 256); mbar_wait(bars + 8 * B_GO, 0); }
        ssm_kgen(sp, R, tid, 1 + wg);
        TS(1);
        float acc[4][16];
        zero_regs(acc[0]); zero_regs(acc[1]); zero_regs(acc[2]); zero_regs(acc[3]);
        if (!(gemm && wg >= 2)) bar_sync(8 + wg, 256);
        mbar_wait(bars + 8 * (B_U + (wg >> 1)), 0);
        bar_sync(1 + wg, 128);
        TS(2);
        ssm_conv(acc, R, R + R_U, tid, 1 + wg);
        TS(12);
    }
    const int head = 4 * wg + w;
    uint32_t q0[4] = {}, q1[4] = {};
    bool ok = false;
    float o[16];
    zero_regs(o);
    mbar_arrive(bars + 8 * B_RFREE);
    if (wg >= k0) cluster_wait();
    if (!xtra) {
    mbar_wait(bars + 8 * B_READY, 0);
    TS(29);
        const uint32_t qa = sb + OFF_W + g * (2 * QP) + head * (2 * DH) + 4 * t, qb = qa + 8 * (2 * QP);
        q0[0] = lds32(qa); q0[1] = lds32(qb); q0[2] = lds32(qa + 16); q0[3] = lds32(qb + 16);
        q1[0] = lds32(qa + 32); q1[1] = lds32(qb + 32);
        q1[2] = t < 2 ? lds32(qa + 48) : 0u; q1[3] = t < 2 ? lds32(qb + 48) : 0u;
        mbar_arrive(bars + 8 * B_QDONE);
        uint32_t h0 = 0, h1 = 0;
#pragma unroll
        for (int i = 0; i < 4; i += 2) {
            uint32_t a;
            a = q0[i] + 0x1E001E00u;     asm("fma.rn.bf16x2 %0, %1, %1, %0;" : "+r"(h0) : "r"(a));
            a = q1[i] + 0x1E001E00u;     asm("fma.rn.bf16x2 %0, %1, %1, %0;" : "+r"(h0) : "r"(a));
            a = q0[i + 1] + 0x1E001E00u; asm("fma.rn.bf16x2 %0, %1, %1, %0;" : "+r"(h1) : "r"(a));
            a = q1[i + 1] + 0x1E001E00u; asm("fma.rn.bf16x2 %0, %1, %1, %0;" : "+r"(h1) : "r"(a));
        }
        const uint32_t big = (q0[0] | q0[1] | q0[2] | q0[3] | q1[0] | q1[1] | q1[2] | q1[3]) & 0x40004000u;
        float n0 = bf_lo(h0) + bf_hi(h0), n1 = bf_lo(h1) + bf_hi(h1);
        n0 += __shfl_xor_sync(~0u, n0, 1); n0 += __shfl_xor_sync(~0u, n0, 2);
        n1 += __shfl_xor_sync(~0u, n1, 1); n1 += __shfl_xor_sync(~0u, n1, 2);
        mbar_wait(bars + 8 * B_KN, 0);
        const float kmax2 = __uint_as_float(lds32(sb + OFF_MISC - 16)), vmax2 = __uint_as_float(lds32(sb + OFF_MISC - 12));
        float r0, r1;
        asm("sqrt.approx.f32 %0, %1;" : "=f"(r0) : "f"(n0 * kmax2));
        asm("sqrt.approx.f32 %0, %1;" : "=f"(r1) : "f"(n1 * kmax2));
        const float m0 = ceilf(r0 * 1.01f + 0.25f), m1 = ceilf(r1 * 1.01f + 0.25f);
        ok = (m0 <= 250.f) && (m1 <= 250.f) && (vmax2 <= 0x1p60f) && big == 0;
        if (t == 2) { q1[2] = pack_bf16((64.f - m0) * 0x1p-60f, 0x1p-60f); q1[3] = pack_bf16((64.f - m1) * 0x1p-60f, 0x1p-60f); }
    }
    if (xtra) return;
    {
        ExpC ec; ec.one = 0x3C003C00u; ec.c3 = 0x2CFA2CFAu;
        asm volatile("" : "+r"(ec.one), "+r"(ec.c3));
        float s[32];
        uint32_t p[4][4], pa[4], pc[4];
        const Desc dk_base = make_desc(sb + OFF_RING, 1024, 128, 0), dv_base = make_desc(sb + OFF_RING + 4096, 128, 1024, 0);
        mbar_wait(bars + 8 * B_KFULL, 0);
        TS(4);
        wg_fence();
        wg_qk(s, q0, dk_base, 0);
        wg_qk(s, q1, dk_base + 128, 1);
        wg_commit();
        wg_wait<0>();
        fence_regs(s);
#pragma unroll 1
        for (int j = 0; j < 4; j++) {
#pragma unroll
            for (int slot = 0; slot < 4; slot++) {
                const int nslot = (slot + 1) & 3, prev = (slot + 3) & 3;
                const Desc dk = dk_base + slot * 1024, dv = dv_base + slot * 1024, dn = dk_base + nslot * 1024;
                exp_quads<(POLY_MASK & 255), 0, 1>(s, pa, p, ec);
                wg_wait<0>();
                release_all(bars + 8 * (B_KEMPTY + prev), peer_bars + 8 * (B_KEMPTY + prev));
                exp_quads<(POLY_MASK & 255), 1, 4>(s, pa, p, ec);
                wg_fence();
                wg_qk(s, q0, dk + 512, 0);
                wg_qk(s, q1, dk + 512 + 128, 1);
                wg_commit();
                wg_fence();
                pv_block(o, pa, p, dv);
                wg_commit();
                mbar_wait(bars + 8 * (B_KFULL + ((slot < 3 || j < 3) ? nslot : 3)), (slot < 3 ? j : min(j + 1, 3)) & 1);
                wg_wait<1>();
                fence_regs(s);
                exp_quads<(POLY_MASK >> 8), 0, 1>(s, pc, p, ec);
                wg_wait<0>();
                exp_quads<(POLY_MASK >> 8), 1, 4>(s, pc, p, ec);
                wg_fence();
                wg_qk(s, q0, dn, 0);
                wg_qk(s, q1, dn + 128, 1);
                wg_commit();
                wg_fence();
                pv_block(o, pc, p, dv + 512);
                wg_commit();
                wg_wait<1>();
                fence_regs(s);
            }
            TS(16 + j);
        }
        wg_wait<0>();
        fence_regs(o);
        release_all(bars + 8 * (B_KEMPTY + 3), peer_bars + 8 * (B_KEMPTY + 3));
    }
    TS(5);
    {
        const uint32_t omat = sb + OFF_O;
        const float l0 = __shfl_sync(~0u, o[12], (lane & ~3) + 2), l1 = __shfl_sync(~0u, o[14], (lane & ~3) + 2);
        ok = ok && (l0 >= 0x1p40f) && (l0 <= 0x1p120f) && (l1 >= 0x1p40f) && (l1 <= 0x1p120f);
        mbar_wait(bars + 8 * B_YDONE, 0);
        if (__all_sync(~0u, ok)) {
            const float i0 = __fdividef(1.f, l0), i1 = __fdividef(1.f, l1);
#pragma unroll
            for (int jb = 0; jb < 4; jb++) {
                if (jb < 3 || t < 2) {
                    const int k = head * DH + 8 * jb + 2 * t;
                    const uint32_t a = omat + (2 * rank) * 7168 + (k >> 3) * 128 + g * 16 + (k & 7) * 2;
                    sts32(a, pack_bf16(o[4 * jb] * i0, o[4 * jb + 1] * i0));
                    sts32(a + 7168, pack_bf16(o[4 * jb + 2] * i1, o[4 * jb + 3] * i1));
                }
            }
        } else {
            attn_fallback(omat, 16 * cta, head, 2 * rank, lane);
        }
        fence_async_smem();
        bar_sync(1 + wg, 128);
        if (tid == 0) {
            const uint32_t src = omat + (2 * rank) * 7168 + wg * 1792;
            bulk_s2s(mapa(src, rank ^ 1), src, 1792, peer_bars + 8 * (B_OFULL + wg));
            bulk_s2s(mapa(src + 7168, rank ^ 1), src + 7168, 1792, peer_bars + 8 * (B_OFULL + wg));
            mbar_arrive(bars + 8 * (B_OFULL + wg));
        }
    }
    {
        float acc[16];
        zero_regs(acc);
        mbar_wait(bars + 8 * B_WO, 0);
        const Desc db = make_desc(sb + OFF_O, 128, 7168, 0);
#pragma unroll 1
        for (int i = 0; i < 7; i++) {
            const int kc = i;
            mbar_wait(bars + 8 * (B_OFULL + ((i + 1) >> 1)), 0);
            if (i == 0) TS(6);
            int late;
            const uint32_t a = sb + wo_box(wg, i, late);
            if (late >= 0) mbar_wait(bars + 8 * (B_KFULL + late), 0);
            const Desc da = wg < 3 ? make_desc(a, 0, 1024, 1) : make_desc(a, 0, 512, 2);
            const int astep = wg < 3 ? 128 : 64;
            wg_fence();
#pragma unroll
            for (int ks = 0; ks < 4; ks++) wg_oproj(acc, da + ks * astep, db + (kc * 4 + ks) * 16, 1);
            wg_commit();
        }
        wg_wait<0>();
        fence_regs(acc);
        TS(7);
        cluster_arrive();
        bar_sync(1 + wg, 128);
        int late;
        const uint32_t st = sb + wo_box(wg, 0, late);
#pragma unroll
        for (int jb = 0; jb < 4; jb += 2) {
            const int pos = 8 * (jb + (lane >> 4)) + (lane & 7), ch = 2 * w + ((lane >> 3) & 1);
            asm volatile("stmatrix.sync.aligned.m8n8.x4.trans.shared.b16 [%0], {%1,%2,%3,%4};" ::"r"(st + pos * 128 + ((ch ^ (lane & 7)) << 4)),
                         "r"(pack_bf16(acc[4 * jb], acc[4 * jb + 1])), "r"(pack_bf16(acc[4 * jb + 2], acc[4 * jb + 3])),
                         "r"(pack_bf16(acc[4 * jb + 4], acc[4 * jb + 5])), "r"(pack_bf16(acc[4 * jb + 6], acc[4 * jb + 7])) : "memory");
        }
        fence_async_smem();
        bar_sync(1 + wg, 128);
        if (tid == 0) {
            asm volatile("cp.async.bulk.tensor.2d.global.shared::cta.bulk_group [%0, {%2, %3}], [%1];"
                         ::"l"(wg < 3 ? &P.tm_o64 : &P.tm_o32), "r"(st), "r"(224 * rank + 64 * wg), "r"(32 * cl) : "memory");
            asm volatile("cp.async.bulk.commit_group;\ncp.async.bulk.wait_group.read 0;" ::: "memory");
        }
        __syncwarp();
        cluster_wait();
    }
    TS(8);
}

typedef CUresult (*EncodeFn)(CUtensorMap*, CUtensorMapDataType, cuuint32_t, void*, const cuuint64_t*, const cuuint64_t*,
                             const cuuint32_t*, const cuuint32_t*, CUtensorMapInterleave, CUtensorMapSwizzle,
                             CUtensorMapL2promotion, CUtensorMapFloatOOBfill);

void encode2d(EncodeFn fn, CUtensorMap* tm, const void* base, int cols, int rows, int boxc, int boxr, CUtensorMapSwizzle sw) {
    cuuint64_t dims[2] = {(cuuint64_t)cols, (cuuint64_t)rows};
    cuuint64_t strides[1] = {(cuuint64_t)cols * 2};
    cuuint32_t box[2] = {(cuuint32_t)boxc, (cuuint32_t)boxr};
    cuuint32_t es[2] = {1, 1};
    fn(tm, CU_TENSOR_MAP_DATA_TYPE_BFLOAT16, 2, const_cast<void*>(base), dims, strides, box, es, CU_TENSOR_MAP_INTERLEAVE_NONE, sw,
       CU_TENSOR_MAP_L2_PROMOTION_L2_128B, CU_TENSOR_MAP_FLOAT_OOB_FILL_NONE);
}

}

extern "C" void kernel_launch(void* const* d_in, const int* in_sizes, int n_in, void* d_out, int out_size) {
    static EncodeFn enc = nullptr;
    static void *q_ptr = nullptr, *y_ptr = nullptr, *ut_ptr = nullptr;
    if (!enc) {
        void* fn = nullptr;
        cudaDriverEntryPointQueryResult st;
        cudaGetDriverEntryPoint("cuTensorMapEncodeTiled", &fn, cudaEnableDefault, &st);
        enc = (EncodeFn)fn;
        cudaFuncSetAttribute(fused_kernel, cudaFuncAttributeMaxDynamicSharedMemorySize, SMEM_BYTES);
        cudaGetSymbolAddress(&q_ptr, g_q);
        cudaGetSymbolAddress(&y_ptr, g_y);
        cudaGetSymbolAddress(&ut_ptr, g_ut);
    }
    Params P;
    encode2d(enc, &P.tm_x, d_in[0], DM, SEQ, 64, 64, CU_TENSOR_MAP_SWIZZLE_128B);
    encode2d(enc, &P.tm_u, d_in[5], DM, SEQ, 64, 32, CU_TENSOR_MAP_SWIZZLE_128B);
    encode2d(enc, &P.tm_ut, ut_ptr, 1088, 2 * DM, 16, 128, CU_TENSOR_MAP_SWIZZLE_32B);
    encode2d(enc, &P.tm_wo64, d_in[4], DM, DM, 64, 64, CU_TENSOR_MAP_SWIZZLE_128B);
    encode2d(enc, &P.tm_wo32, d_in[4], DM, DM, 32, 64, CU_TENSOR_MAP_SWIZZLE_64B);
    encode2d(enc, &P.tm_wq, d_in[1], DM, DM, 64, 64, CU_TENSOR_MAP_SWIZZLE_128B);
    encode2d(enc, &P.tm_q, q_ptr, QP, SEQ, 64, 64, CU_TENSOR_MAP_SWIZZLE_128B);
    encode2d(enc, &P.tm_o64, d_out, 2 * DM, SEQ, 64, 32, CU_TENSOR_MAP_SWIZZLE_128B);
    encode2d(enc, &P.tm_o32, d_out, 2 * DM, SEQ, 32, 32, CU_TENSOR_MAP_SWIZZLE_128B);
    encode2d(enc, &P.tm_y, y_ptr, 1088, 2 * DM, 8, 224, CU_TENSOR_MAP_SWIZZLE_NONE);
    P.wk = (const __nv_bfloat16*)d_in[2]; P.wv = (const __nv_bfloat16*)d_in[3];
    P.lar = (const __nv_bfloat16*)d_in[6]; P.aim = (const __nv_bfloat16*)d_in[7];
    P.cre = (const __nv_bfloat16*)d_in[8]; P.cim = (const __nv_bfloat16*)d_in[9];
    P.ldt = (const __nv_bfloat16*)d_in[10]; P.dsk = (const __nv_bfloat16*)d_in[11];
    P.out = (__nv_bfloat16*)d_out;
    fused_kernel<<<NCTA, NTHR, SMEM_BYTES>>>(P);
}
```
